```python
import torch

def _softmax(x, axis=-1):
    return torch.softmax(x, dim=axis)
def _gelu(x):
    return torch.nn.functional.gelu(x, approximate="tanh")
def _silu(x):
    return torch.nn.functional.silu(x)
def _sigmoid(x):
    return torch.sigmoid(x)
def _layernorm(x, axis=-1, eps=1e-5):
    m = x.mean(dim=axis, keepdim=True)
    v = x.var(dim=axis, keepdim=True, unbiased=False)
    return (x - m) / torch.sqrt(v + eps)
def _scatter_add(tgt, idx, src, axis=0):
    return tgt.clone().index_add_(axis, idx, src)
def _segment_sum(src, seg, n):
    out = torch.zeros((n,) + src.shape[1:], dtype=src.dtype)
    return out.index_add_(0, seg, src)
def _pad(x, pw):
    flat = tuple(v for pair in reversed(pw) for v in pair)
    return torch.nn.functional.pad(x, flat)

kernel_name = 'gated_mix__ssm_conv_h3__glu_gated_glu__prompt'

def setup_inputs():

    _w = (lambda a: (lambda t: t.to(torch.bfloat16) if t.is_floating_point() else t)(torch.as_tensor(a)))
    def _A_setup():
        B, S, D = 1, 2048, 640
        ks = 4
        return {
            "q": _w((lambda *s: torch.randn(*s, dtype=torch.bfloat16) * 0.05)(B, S, D)),
            "k": _w((lambda *s: torch.randn(*s, dtype=torch.bfloat16) * 0.4)(B, S, D)),
            "v": _w((lambda *s: torch.randn(*s, dtype=torch.bfloat16) * 0.4)(B, S, D)),
            "shift_k": _w((lambda *s: torch.randn(*s, dtype=torch.bfloat16) * 0.4)(D, ks) * 0.5),
            "ssm_k": _w((lambda *s: torch.randn(*s, dtype=torch.bfloat16) * 1.6)(D, S) * (1.0 / S ** 0.5)),
            "ssm_D": _w((lambda *s: torch.randn(*s, dtype=torch.bfloat16) * 0.4)(D)),
        }
    _A_in = _A_setup()

    def _B_setup():
        B, S, D, F = 1, 2048, 640, 1536
        return {
            "x": _w((lambda *s: torch.randn(*s, dtype=torch.bfloat16) * 0.05)(B, S, D)),
            "w_gate": _w((lambda *s: torch.randn(*s, dtype=torch.bfloat16) * 0.4)(D, F)),
            "w_up": _w((lambda *s: torch.randn(*s, dtype=torch.bfloat16) * 0.05)(D, F)),
            "w_down": _w((lambda *s: torch.randn(*s, dtype=torch.bfloat16) * 0.05)(F, D)),
        }
    _B_in = _B_setup()

    return {
        "A_q": _A_in["q"],
        "A_k": _A_in["k"],
        "A_v": _A_in["v"],
        "A_shift_k": _A_in["shift_k"],
        "A_ssm_k": _A_in["ssm_k"],
        "A_ssm_D": _A_in["ssm_D"],
        "B_x": _B_in["x"],
        "B_w_gate": _B_in["w_gate"],
        "B_w_up": _B_in["w_up"],
        "B_w_down": _B_in["w_down"],
        "gate_w": _w((lambda *s: torch.randn(*s, dtype=torch.bfloat16) * 0.05)(640) * 16.0),
    }

def reference(A_q, A_k, A_v, A_shift_k, A_ssm_k, A_ssm_D, B_x, B_w_gate, B_w_up, B_w_down, gate_w):
    def _A_ref(q, k, v, shift_k, ssm_k, ssm_D):
        B, S, D = q.shape
        ks = shift_k.shape[-1]
        k_pad = _pad(k, ((0, 0), (ks - 1, 0), (0, 0)))
        k_shift = torch.zeros_like(k)
        for t in range(ks):
            k_shift = k_shift + k_pad[:, t:t + S, :] * shift_k[:, ks - 1 - t][None, None, :]
        kv = k_shift * v
        L = 2 * S
        kv_pad = _pad(kv, ((0, 0), (0, S), (0, 0)))
        kf_pad = _pad(ssm_k, ((0, 0), (0, S)))
        kv_f = (lambda x, axes=(-2,-1): torch.fft.rfft2(x.float(), dim=axes))(kv_pad[:, None, :, :], axes=(1, 2))
        kf_f = (lambda x, axes=(-2,-1): torch.fft.rfft2(x.float(), dim=axes))(kf_pad[:, None, :], axes=(1, 2))
        kf_f = (lambda x, *d: x.permute(*d))(kf_f, 1, 2, 0)
        y_f = kv_f * kf_f[None, :, :, :]
        y = (lambda x, s, axes=(-2,-1): torch.fft.irfft2(x, s=s, dim=axes).to(torch.bfloat16))(y_f, (1, L), axes=(1, 2))[:, 0, :S, :]
        y = y + kv * ssm_D[None, None, :]
        return q * y

    def _B_ref(x, w_gate, w_up, w_down):
        g = torch.einsum("bsd,df->bsf", x, w_gate)
        u = torch.einsum("bsd,df->bsf", x, w_up)
        h = _sigmoid(g) * u
        return torch.einsum("bsf,fd->bsd", h, w_down)

    x = A_q
    g = _sigmoid((x * gate_w).sum(-1, keepdims=True))
    a = _A_ref(x, A_k, A_v, A_shift_k, A_ssm_k, A_ssm_D)
    b = _B_ref(x, B_w_gate, B_w_up, B_w_down)
    return g * a + (1 - g) * b
```

```cpp
#include <cuda_runtime.h>
#include <cuda_bf16.h>
#include <cuda.h>
#include <stdint.h>

namespace {

constexpr int XP = 2240;
constexpr int XCH = 2 * XP;
constexpr int PP = 2496;
constexpr int HC = 4128;
#define C0 2

constexpr uint32_t SM_W = 0;
constexpr uint32_t SM_X = 122880;
constexpr uint32_t SM_R2 = 73728;
constexpr uint32_t SM_D = 188416;
constexpr uint32_t SM_BAR = 231296;
constexpr uint32_t SM_TOTAL = 231296 + 512;
enum { B_FW = 0, B_EW = 5, B_FX = 10, B_EX = 13, B_KV = 16, B_XI = 17, B_HC = 18, B_F2 = 19, B_E2 = 23, B_Q = 27, B_Z = 28,
       B_HS = 29  , B_HF = 31  , B_CD = 33  , B_GA = 35, B_PRE = 36, B_G1 = 37, B_N = 38 };

__device__ __align__(1024) uint8_t g_X[640 * XCH];
__device__ __align__(1024) uint8_t g_h[2048 * 1536 * 2];
__device__ __align__(1024) __nv_bfloat16 g_zT[640 * 2048];
__device__ float g_gate[2048];
__device__ uint32_t g_cnt[40 * 32];
#define TS(i)
#define TS1(i)

struct Maps { CUtensorMap x, wg, wu, wd, k, v, q, z, o; };
struct Ptrs { const __nv_bfloat16 *x, *shift_k, *ssm_k, *ssm_D, *gate_w, *wd; };

__device__ __forceinline__ uint32_t smem_u32(const void* p) { return (uint32_t)__cvta_generic_to_shared(p); }
__device__ __forceinline__ void mbar_init(uint32_t bar, uint32_t cnt) { asm volatile("mbarrier.init.shared::cta.b64 [%0], %1;" ::"r"(bar), "r"(cnt)); }
__device__ __forceinline__ void mbar_expect_tx(uint32_t bar, uint32_t bytes) { asm volatile("mbarrier.arrive.expect_tx.shared::cta.b64 _, [%0], %1;" ::"r"(bar), "r"(bytes) : "memory"); }
__device__ __forceinline__ void mbar_arrive(uint32_t bar) { asm volatile("mbarrier.arrive.shared::cta.b64 _, [%0];" ::"r"(bar) : "memory"); }
__device__ __forceinline__ void mbar_wait(uint32_t bar, uint32_t parity) {
  uint32_t ok;
  asm volatile("{.reg .pred p; mbarrier.try_wait.parity.shared::cta.b64 p, [%1], %2; selp.u32 %0,1,0,p;}" : "=r"(ok) : "r"(bar), "r"(parity) : "memory");
  if (!ok) {
    uint32_t it = 0;
    do {
      asm volatile("{.reg .pred p; mbarrier.try_wait.parity.shared::cta.b64 p, [%1], %2, 2000; selp.u32 %0,1,0,p;}" : "=r"(ok) : "r"(bar), "r"(parity) : "memory");
    } while (!ok && ++it < 100000u);
  }
}
__device__ __forceinline__ void flag_wait(const uint32_t* p, uint32_t target) {
  uint32_t v, it = 0;
  while (true) {
    asm volatile("ld.acquire.gpu.global.u32 %0, [%1];" : "=r"(v) : "l"(p) : "memory");
    if ((int)(v - target) >= 0) break;
    if (++it > 400000u) break;
    __nanosleep(40);
  }
  asm volatile("fence.proxy.async;" ::: "memory");
}
__device__ __forceinline__ void flag_add(uint32_t* p, uint32_t v) {
  asm volatile("fence.proxy.async;" ::: "memory");
  asm volatile("fence.acq_rel.gpu;" ::: "memory");
  asm volatile("red.relaxed.gpu.global.add.u32 [%0], %1;" ::"l"(p), "r"(v) : "memory");
}
__device__ __forceinline__ void tma2d(uint32_t dst, const CUtensorMap* m, uint32_t bar, int c0, int c1) {
  asm volatile("cp.async.bulk.tensor.2d.shared::cluster.global.mbarrier::complete_tx::bytes [%0], [%1, {%3,%4}], [%2];" ::"r"(dst), "l"(m), "r"(bar), "r"(c0), "r"(c1) : "memory");
}
__device__ __forceinline__ void tma3d(uint32_t dst, const CUtensorMap* m, uint32_t bar, int c0, int c1, int c2) {
  asm volatile("cp.async.bulk.tensor.3d.shared::cluster.global.mbarrier::complete_tx::bytes [%0], [%1, {%3,%4,%5}], [%2];" ::"r"(dst), "l"(m), "r"(bar), "r"(c0), "r"(c1), "r"(c2) : "memory");
}
__device__ __forceinline__ void tma3d_store(const CUtensorMap* m, uint32_t src, int c0, int c1, int c2) {
  asm volatile("cp.async.bulk.tensor.3d.global.shared::cta.bulk_group [%0, {%2,%3,%4}], [%1];" ::"l"(m), "r"(src), "r"(c0), "r"(c1), "r"(c2) : "memory");
}
__device__ __forceinline__ void bulk_g2s(uint32_t dst, const void* src, uint32_t bytes, uint32_t bar) {
  asm volatile("cp.async.bulk.shared::cluster.global.mbarrier::complete_tx::bytes [%0], [%1], %2, [%3];" ::"r"(dst), "l"(src), "r"(bytes), "r"(bar) : "memory");
}
__device__ __forceinline__ void bulk_s2g(void* dst, uint32_t src, uint32_t bytes) {
  asm volatile("cp.async.bulk.global.shared::cta.bulk_group [%0], [%1], %2;" ::"l"(dst), "r"(src), "r"(bytes) : "memory");
}
__device__ __forceinline__ void l2_prefetch(const void* src, uint32_t bytes) {
  asm volatile("cp.async.bulk.prefetch.L2.global [%0], %1;" ::"l"(src), "r"(bytes) : "memory");
}
__device__ __forceinline__ void tmap_prefetch(const CUtensorMap* m) { asm volatile("prefetch.tensormap [%0];" ::"l"(m) : "memory"); }
__device__ __forceinline__ uint64_t mkdesc(uint32_t addr, uint32_t lbo, uint32_t sbo, uint32_t swz) {
  return (uint64_t)((addr & 0x3FFFF) >> 4) | ((uint64_t)(lbo >> 4) << 16) | ((uint64_t)(sbo >> 4) << 32) | ((uint64_t)swz << 62);
}
#define WG_FENCE() asm volatile("wgmma.fence.sync.aligned;" ::: "memory")
#define WG_COMMIT() asm volatile("wgmma.commit_group.sync.aligned;" ::: "memory")
#define WG_WAIT(n) asm volatile("wgmma.wait_group.sync.aligned " #n ";" ::: "memory")
__device__ __forceinline__ void bar_sync(int id, int n) { asm volatile("bar.sync %0, %1;" ::"r"(id), "r"(n) : "memory"); }
__device__ __forceinline__ void bar_arrive(int id, int n) { asm volatile("bar.arrive %0, %1;" ::"r"(id), "r"(n) : "memory"); }
__device__ __forceinline__ uint32_t pack_bf16(float lo, float hi) { uint32_t r; asm("cvt.rn.bf16x2.f32 %0, %1, %2;" : "=r"(r) : "f"(hi), "f"(lo)); return r; }
__device__ __forceinline__ uint32_t bmul2(uint32_t a, uint32_t b) { uint32_t r; asm("mul.rn.bf16x2 %0, %1, %2;" : "=r"(r) : "r"(a), "r"(b)); return r; }
__device__ __forceinline__ uint32_t badd2(uint32_t a, uint32_t b) { uint32_t r; asm("add.rn.bf16x2 %0, %1, %2;" : "=r"(r) : "r"(a), "r"(b)); return r; }
__device__ __forceinline__ uint32_t lds32(uint32_t a) { uint32_t r; asm volatile("ld.shared.u32 %0, [%1];" : "=r"(r) : "r"(a)); return r; }
__device__ __forceinline__ uint4 lds128(uint32_t a) { uint4 v; asm volatile("ld.shared.v4.u32 {%0,%1,%2,%3}, [%4];" : "=r"(v.x), "=r"(v.y), "=r"(v.z), "=r"(v.w) : "r"(a)); return v; }
__device__ __forceinline__ void sts128(uint32_t a, uint32_t x, uint32_t y, uint32_t z, uint32_t w) { asm volatile("st.shared.v4.u32 [%0], {%1,%2,%3,%4};" ::"r"(a), "r"(x), "r"(y), "r"(z), "r"(w) : "memory"); }
__device__ __forceinline__ void stsm4(uint32_t a, uint32_t x, uint32_t y, uint32_t z, uint32_t w) { asm volatile("stmatrix.sync.aligned.m8n8.x4.shared.b16 [%0], {%1,%2,%3,%4};" ::"r"(a), "r"(x), "r"(y), "r"(z), "r"(w) : "memory"); }
__device__ __forceinline__ void stsm4t(uint32_t a, uint32_t x, uint32_t y, uint32_t z, uint32_t w) { asm volatile("stmatrix.sync.aligned.m8n8.x4.trans.shared.b16 [%0], {%1,%2,%3,%4};" ::"r"(a), "r"(x), "r"(y), "r"(z), "r"(w) : "memory"); }
__device__ __forceinline__ uint4 ldsm4(uint32_t a) { uint4 v; asm volatile("ldmatrix.sync.aligned.m8n8.x4.shared.b16 {%0,%1,%2,%3}, [%4];" : "=r"(v.x), "=r"(v.y), "=r"(v.z), "=r"(v.w) : "r"(a) : "memory"); return v; }
__device__ __forceinline__ uint4 ldsm4t(uint32_t a) { uint4 v; asm volatile("ldmatrix.sync.aligned.m8n8.x4.trans.shared.b16 {%0,%1,%2,%3}, [%4];" : "=r"(v.x), "=r"(v.y), "=r"(v.z), "=r"(v.w) : "r"(a) : "memory"); return v; }
__device__ __forceinline__ float sigmoidf_fast(float x) {
  float e, r;
  asm("ex2.approx.ftz.f32 %0, %1;" : "=f"(e) : "f"(x * -1.4426950408889634f));
  asm("rcp.approx.ftz.f32 %0, %1;" : "=f"(r) : "f"(1.0f + e));
  return r;
}

__device__ __forceinline__ void wgmma_ss_tb_n192(float* d, uint64_t da, uint64_t db, int sc) {
  asm volatile("{.reg .pred p; setp.ne.b32 p, %98, 0;\n"
   "wgmma.mma_async.sync.aligned.m64n192k16.f32.bf16.bf16 {%0,%1,%2,%3,%4,%5,%6,%7,%8,%9,%10,%11,%12,%13,%14,%15,%16,%17,%18,%19,%20,%21,%22,%23,%24,%25,%26,%27,%28,%29,%30,%31,%32,%33,%34,%35,%36,%37,%38,%39,%40,%41,%42,%43,%44,%45,%46,%47,%48,%49,%50,%51,%52,%53,%54,%55,%56,%57,%58,%59,%60,%61,%62,%63,%64,%65,%66,%67,%68,%69,%70,%71,%72,%73,%74,%75,%76,%77,%78,%79,%80,%81,%82,%83,%84,%85,%86,%87,%88,%89,%90,%91,%92,%93,%94,%95}, %96, %97, p, 1, 1, 0, 1;}\n"
   : "+f"(d[0]),"+f"(d[1]),"+f"(d[2]),"+f"(d[3]),"+f"(d[4]),"+f"(d[5]),"+f"(d[6]),"+f"(d[7]),"+f"(d[8]),"+f"(d[9]),"+f"(d[10]),"+f"(d[11]),"+f"(d[12]),"+f"(d[13]),"+f"(d[14]),"+f"(d[15]),"+f"(d[16]),"+f"(d[17]),"+f"(d[18]),"+f"(d[19]),"+f"(d[20]),"+f"(d[21]),"+f"(d[22]),"+f"(d[23]),"+f"(d[24]),"+f"(d[25]),"+f"(d[26]),"+f"(d[27]),"+f"(d[28]),"+f"(d[29]),"+f"(d[30]),"+f"(d[31]),"+f"(d[32]),"+f"(d[33]),"+f"(d[34]),"+f"(d[35]),"+f"(d[36]),"+f"(d[37]),"+f"(d[38]),"+f"(d[39]),"+f"(d[40]),"+f"(d[41]),"+f"(d[42]),"+f"(d[43]),"+f"(d[44]),"+f"(d[45]),"+f"(d[46]),"+f"(d[47]),"+f"(d[48]),"+f"(d[49]),"+f"(d[50]),"+f"(d[51]),"+f"(d[52]),"+f"(d[53]),"+f"(d[54]),"+f"(d[55]),"+f"(d[56]),"+f"(d[57]),"+f"(d[58]),"+f"(d[59]),"+f"(d[60]),"+f"(d[61]),"+f"(d[62]),"+f"(d[63]),"+f"(d[64]),"+f"(d[65]),"+f"(d[66]),"+f"(d[67]),"+f"(d[68]),"+f"(d[69]),"+f"(d[70]),"+f"(d[71]),"+f"(d[72]),"+f"(d[73]),"+f"(d[74]),"+f"(d[75]),"+f"(d[76]),"+f"(d[77]),"+f"(d[78]),"+f"(d[79]),"+f"(d[80]),"+f"(d[81]),"+f"(d[82]),"+f"(d[83]),"+f"(d[84]),"+f"(d[85]),"+f"(d[86]),"+f"(d[87]),"+f"(d[88]),"+f"(d[89]),"+f"(d[90]),"+f"(d[91]),"+f"(d[92]),"+f"(d[93]),"+f"(d[94]),"+f"(d[95]) : "l"(da), "l"(db), "r"(sc));
}
__device__ __forceinline__ void wgmma_ss_tb_n160(float* d, uint64_t da, uint64_t db, int sc) {
  asm volatile("{.reg .pred p; setp.ne.b32 p, %82, 0;\n"
   "wgmma.mma_async.sync.aligned.m64n160k16.f32.bf16.bf16 {%0,%1,%2,%3,%4,%5,%6,%7,%8,%9,%10,%11,%12,%13,%14,%15,%16,%17,%18,%19,%20,%21,%22,%23,%24,%25,%26,%27,%28,%29,%30,%31,%32,%33,%34,%35,%36,%37,%38,%39,%40,%41,%42,%43,%44,%45,%46,%47,%48,%49,%50,%51,%52,%53,%54,%55,%56,%57,%58,%59,%60,%61,%62,%63,%64,%65,%66,%67,%68,%69,%70,%71,%72,%73,%74,%75,%76,%77,%78,%79}, %80, %81, p, 1, 1, 0, 1;}\n"
   : "+f"(d[0]),"+f"(d[1]),"+f"(d[2]),"+f"(d[3]),"+f"(d[4]),"+f"(d[5]),"+f"(d[6]),"+f"(d[7]),"+f"(d[8]),"+f"(d[9]),"+f"(d[10]),"+f"(d[11]),"+f"(d[12]),"+f"(d[13]),"+f"(d[14]),"+f"(d[15]),"+f"(d[16]),"+f"(d[17]),"+f"(d[18]),"+f"(d[19]),"+f"(d[20]),"+f"(d[21]),"+f"(d[22]),"+f"(d[23]),"+f"(d[24]),"+f"(d[25]),"+f"(d[26]),"+f"(d[27]),"+f"(d[28]),"+f"(d[29]),"+f"(d[30]),"+f"(d[31]),"+f"(d[32]),"+f"(d[33]),"+f"(d[34]),"+f"(d[35]),"+f"(d[36]),"+f"(d[37]),"+f"(d[38]),"+f"(d[39]),"+f"(d[40]),"+f"(d[41]),"+f"(d[42]),"+f"(d[43]),"+f"(d[44]),"+f"(d[45]),"+f"(d[46]),"+f"(d[47]),"+f"(d[48]),"+f"(d[49]),"+f"(d[50]),"+f"(d[51]),"+f"(d[52]),"+f"(d[53]),"+f"(d[54]),"+f"(d[55]),"+f"(d[56]),"+f"(d[57]),"+f"(d[58]),"+f"(d[59]),"+f"(d[60]),"+f"(d[61]),"+f"(d[62]),"+f"(d[63]),"+f"(d[64]),"+f"(d[65]),"+f"(d[66]),"+f"(d[67]),"+f"(d[68]),"+f"(d[69]),"+f"(d[70]),"+f"(d[71]),"+f"(d[72]),"+f"(d[73]),"+f"(d[74]),"+f"(d[75]),"+f"(d[76]),"+f"(d[77]),"+f"(d[78]),"+f"(d[79]) : "l"(da), "l"(db), "r"(sc));
}
template<int N> __device__ __forceinline__ void wgmma_rs(float* d, const uint32_t* a, uint64_t db, int sc);
template<> __device__ __forceinline__ void wgmma_rs<128>(float* d, const uint32_t* a, uint64_t db, int sc) {
  asm volatile("{.reg .pred p; setp.ne.b32 p, %69, 0;\n"
   "wgmma.mma_async.sync.aligned.m64n128k16.f32.bf16.bf16 {%0,%1,%2,%3,%4,%5,%6,%7,%8,%9,%10,%11,%12,%13,%14,%15,%16,%17,%18,%19,%20,%21,%22,%23,%24,%25,%26,%27,%28,%29,%30,%31,%32,%33,%34,%35,%36,%37,%38,%39,%40,%41,%42,%43,%44,%45,%46,%47,%48,%49,%50,%51,%52,%53,%54,%55,%56,%57,%58,%59,%60,%61,%62,%63}, {%64,%65,%66,%67}, %68, p, 1, 1, 0;}\n"
   : "+f"(d[0]),"+f"(d[1]),"+f"(d[2]),"+f"(d[3]),"+f"(d[4]),"+f"(d[5]),"+f"(d[6]),"+f"(d[7]),"+f"(d[8]),"+f"(d[9]),"+f"(d[10]),"+f"(d[11]),"+f"(d[12]),"+f"(d[13]),"+f"(d[14]),"+f"(d[15]),"+f"(d[16]),"+f"(d[17]),"+f"(d[18]),"+f"(d[19]),"+f"(d[20]),"+f"(d[21]),"+f"(d[22]),"+f"(d[23]),"+f"(d[24]),"+f"(d[25]),"+f"(d[26]),"+f"(d[27]),"+f"(d[28]),"+f"(d[29]),"+f"(d[30]),"+f"(d[31]),"+f"(d[32]),"+f"(d[33]),"+f"(d[34]),"+f"(d[35]),"+f"(d[36]),"+f"(d[37]),"+f"(d[38]),"+f"(d[39]),"+f"(d[40]),"+f"(d[41]),"+f"(d[42]),"+f"(d[43]),"+f"(d[44]),"+f"(d[45]),"+f"(d[46]),"+f"(d[47]),"+f"(d[48]),"+f"(d[49]),"+f"(d[50]),"+f"(d[51]),"+f"(d[52]),"+f"(d[53]),"+f"(d[54]),"+f"(d[55]),"+f"(d[56]),"+f"(d[57]),"+f"(d[58]),"+f"(d[59]),"+f"(d[60]),"+f"(d[61]),"+f"(d[62]),"+f"(d[63]) : "r"(a[0]), "r"(a[1]), "r"(a[2]), "r"(a[3]), "l"(db), "r"(sc));
}
template<> __device__ __forceinline__ void wgmma_rs<112>(float* d, const uint32_t* a, uint64_t db, int sc) {
  asm volatile("{.reg .pred p; setp.ne.b32 p, %61, 0;\n"
   "wgmma.mma_async.sync.aligned.m64n112k16.f32.bf16.bf16 {%0,%1,%2,%3,%4,%5,%6,%7,%8,%9,%10,%11,%12,%13,%14,%15,%16,%17,%18,%19,%20,%21,%22,%23,%24,%25,%26,%27,%28,%29,%30,%31,%32,%33,%34,%35,%36,%37,%38,%39,%40,%41,%42,%43,%44,%45,%46,%47,%48,%49,%50,%51,%52,%53,%54,%55}, {%56,%57,%58,%59}, %60, p, 1, 1, 0;}\n"
   : "+f"(d[0]),"+f"(d[1]),"+f"(d[2]),"+f"(d[3]),"+f"(d[4]),"+f"(d[5]),"+f"(d[6]),"+f"(d[7]),"+f"(d[8]),"+f"(d[9]),"+f"(d[10]),"+f"(d[11]),"+f"(d[12]),"+f"(d[13]),"+f"(d[14]),"+f"(d[15]),"+f"(d[16]),"+f"(d[17]),"+f"(d[18]),"+f"(d[19]),"+f"(d[20]),"+f"(d[21]),"+f"(d[22]),"+f"(d[23]),"+f"(d[24]),"+f"(d[25]),"+f"(d[26]),"+f"(d[27]),"+f"(d[28]),"+f"(d[29]),"+f"(d[30]),"+f"(d[31]),"+f"(d[32]),"+f"(d[33]),"+f"(d[34]),"+f"(d[35]),"+f"(d[36]),"+f"(d[37]),"+f"(d[38]),"+f"(d[39]),"+f"(d[40]),"+f"(d[41]),"+f"(d[42]),"+f"(d[43]),"+f"(d[44]),"+f"(d[45]),"+f"(d[46]),"+f"(d[47]),"+f"(d[48]),"+f"(d[49]),"+f"(d[50]),"+f"(d[51]),"+f"(d[52]),"+f"(d[53]),"+f"(d[54]),"+f"(d[55]) : "r"(a[0]), "r"(a[1]), "r"(a[2]), "r"(a[3]), "l"(db), "r"(sc));
}
template<> __device__ __forceinline__ void wgmma_rs<96>(float* d, const uint32_t* a, uint64_t db, int sc) {
  asm volatile("{.reg .pred p; setp.ne.b32 p, %53, 0;\n"
   "wgmma.mma_async.sync.aligned.m64n96k16.f32.bf16.bf16 {%0,%1,%2,%3,%4,%5,%6,%7,%8,%9,%10,%11,%12,%13,%14,%15,%16,%17,%18,%19,%20,%21,%22,%23,%24,%25,%26,%27,%28,%29,%30,%31,%32,%33,%34,%35,%36,%37,%38,%39,%40,%41,%42,%43,%44,%45,%46,%47}, {%48,%49,%50,%51}, %52, p, 1, 1, 0;}\n"
   : "+f"(d[0]),"+f"(d[1]),"+f"(d[2]),"+f"(d[3]),"+f"(d[4]),"+f"(d[5]),"+f"(d[6]),"+f"(d[7]),"+f"(d[8]),"+f"(d[9]),"+f"(d[10]),"+f"(d[11]),"+f"(d[12]),"+f"(d[13]),"+f"(d[14]),"+f"(d[15]),"+f"(d[16]),"+f"(d[17]),"+f"(d[18]),"+f"(d[19]),"+f"(d[20]),"+f"(d[21]),"+f"(d[22]),"+f"(d[23]),"+f"(d[24]),"+f"(d[25]),"+f"(d[26]),"+f"(d[27]),"+f"(d[28]),"+f"(d[29]),"+f"(d[30]),"+f"(d[31]),"+f"(d[32]),"+f"(d[33]),"+f"(d[34]),"+f"(d[35]),"+f"(d[36]),"+f"(d[37]),"+f"(d[38]),"+f"(d[39]),"+f"(d[40]),"+f"(d[41]),"+f"(d[42]),"+f"(d[43]),"+f"(d[44]),"+f"(d[45]),"+f"(d[46]),"+f"(d[47]) : "r"(a[0]), "r"(a[1]), "r"(a[2]), "r"(a[3]), "l"(db), "r"(sc));
}
template<> __device__ __forceinline__ void wgmma_rs<80>(float* d, const uint32_t* a, uint64_t db, int sc) {
  asm volatile("{.reg .pred p; setp.ne.b32 p, %45, 0;\n"
   "wgmma.mma_async.sync.aligned.m64n80k16.f32.bf16.bf16 {%0,%1,%2,%3,%4,%5,%6,%7,%8,%9,%10,%11,%12,%13,%14,%15,%16,%17,%18,%19,%20,%21,%22,%23,%24,%25,%26,%27,%28,%29,%30,%31,%32,%33,%34,%35,%36,%37,%38,%39}, {%40,%41,%42,%43}, %44, p, 1, 1, 0;}\n"
   : "+f"(d[0]),"+f"(d[1]),"+f"(d[2]),"+f"(d[3]),"+f"(d[4]),"+f"(d[5]),"+f"(d[6]),"+f"(d[7]),"+f"(d[8]),"+f"(d[9]),"+f"(d[10]),"+f"(d[11]),"+f"(d[12]),"+f"(d[13]),"+f"(d[14]),"+f"(d[15]),"+f"(d[16]),"+f"(d[17]),"+f"(d[18]),"+f"(d[19]),"+f"(d[20]),"+f"(d[21]),"+f"(d[22]),"+f"(d[23]),"+f"(d[24]),"+f"(d[25]),"+f"(d[26]),"+f"(d[27]),"+f"(d[28]),"+f"(d[29]),"+f"(d[30]),"+f"(d[31]),"+f"(d[32]),"+f"(d[33]),"+f"(d[34]),"+f"(d[35]),"+f"(d[36]),"+f"(d[37]),"+f"(d[38]),"+f"(d[39]) : "r"(a[0]), "r"(a[1]), "r"(a[2]), "r"(a[3]), "l"(db), "r"(sc));
}
template<> __device__ __forceinline__ void wgmma_rs<64>(float* d, const uint32_t* a, uint64_t db, int sc) {
  asm volatile("{.reg .pred p; setp.ne.b32 p, %37, 0;\n"
   "wgmma.mma_async.sync.aligned.m64n64k16.f32.bf16.bf16 {%0,%1,%2,%3,%4,%5,%6,%7,%8,%9,%10,%11,%12,%13,%14,%15,%16,%17,%18,%19,%20,%21,%22,%23,%24,%25,%26,%27,%28,%29,%30,%31}, {%32,%33,%34,%35}, %36, p, 1, 1, 0;}\n"
   : "+f"(d[0]),"+f"(d[1]),"+f"(d[2]),"+f"(d[3]),"+f"(d[4]),"+f"(d[5]),"+f"(d[6]),"+f"(d[7]),"+f"(d[8]),"+f"(d[9]),"+f"(d[10]),"+f"(d[11]),"+f"(d[12]),"+f"(d[13]),"+f"(d[14]),"+f"(d[15]),"+f"(d[16]),"+f"(d[17]),"+f"(d[18]),"+f"(d[19]),"+f"(d[20]),"+f"(d[21]),"+f"(d[22]),"+f"(d[23]),"+f"(d[24]),"+f"(d[25]),"+f"(d[26]),"+f"(d[27]),"+f"(d[28]),"+f"(d[29]),"+f"(d[30]),"+f"(d[31]) : "r"(a[0]), "r"(a[1]), "r"(a[2]), "r"(a[3]), "l"(db), "r"(sc));
}
template<> __device__ __forceinline__ void wgmma_rs<48>(float* d, const uint32_t* a, uint64_t db, int sc) {
  asm volatile("{.reg .pred p; setp.ne.b32 p, %29, 0;\n"
   "wgmma.mma_async.sync.aligned.m64n48k16.f32.bf16.bf16 {%0,%1,%2,%3,%4,%5,%6,%7,%8,%9,%10,%11,%12,%13,%14,%15,%16,%17,%18,%19,%20,%21,%22,%23}, {%24,%25,%26,%27}, %28, p, 1, 1, 0;}\n"
   : "+f"(d[0]),"+f"(d[1]),"+f"(d[2]),"+f"(d[3]),"+f"(d[4]),"+f"(d[5]),"+f"(d[6]),"+f"(d[7]),"+f"(d[8]),"+f"(d[9]),"+f"(d[10]),"+f"(d[11]),"+f"(d[12]),"+f"(d[13]),"+f"(d[14]),"+f"(d[15]),"+f"(d[16]),"+f"(d[17]),"+f"(d[18]),"+f"(d[19]),"+f"(d[20]),"+f"(d[21]),"+f"(d[22]),"+f"(d[23]) : "r"(a[0]), "r"(a[1]), "r"(a[2]), "r"(a[3]), "l"(db), "r"(sc));
}
template<> __device__ __forceinline__ void wgmma_rs<32>(float* d, const uint32_t* a, uint64_t db, int sc) {
  asm volatile("{.reg .pred p; setp.ne.b32 p, %21, 0;\n"
   "wgmma.mma_async.sync.aligned.m64n32k16.f32.bf16.bf16 {%0,%1,%2,%3,%4,%5,%6,%7,%8,%9,%10,%11,%12,%13,%14,%15}, {%16,%17,%18,%19}, %20, p, 1, 1, 0;}\n"
   : "+f"(d[0]),"+f"(d[1]),"+f"(d[2]),"+f"(d[3]),"+f"(d[4]),"+f"(d[5]),"+f"(d[6]),"+f"(d[7]),"+f"(d[8]),"+f"(d[9]),"+f"(d[10]),"+f"(d[11]),"+f"(d[12]),"+f"(d[13]),"+f"(d[14]),"+f"(d[15]) : "r"(a[0]), "r"(a[1]), "r"(a[2]), "r"(a[3]), "l"(db), "r"(sc));
}
template<> __device__ __forceinline__ void wgmma_rs<16>(float* d, const uint32_t* a, uint64_t db, int sc) {
  asm volatile("{.reg .pred p; setp.ne.b32 p, %13, 0;\n"
   "wgmma.mma_async.sync.aligned.m64n16k16.f32.bf16.bf16 {%0,%1,%2,%3,%4,%5,%6,%7}, {%8,%9,%10,%11}, %12, p, 1, 1, 0;}\n"
   : "+f"(d[0]),"+f"(d[1]),"+f"(d[2]),"+f"(d[3]),"+f"(d[4]),"+f"(d[5]),"+f"(d[6]),"+f"(d[7]) : "r"(a[0]), "r"(a[1]), "r"(a[2]), "r"(a[3]), "l"(db), "r"(sc));
}

template <int OFF> __device__ __forceinline__ void conv_ldA(uint32_t* A, uint32_t ra, uint32_t zz) {
  A[2] = lds32(ra + OFF);
#pragma unroll
  for (int s = 0; s < 4; s++) { A[4 * s] = lds32(ra + OFF + 32 * s + 16); A[4 * s + 1] = lds32(ra + OFF + 32 * s + 32); }
#pragma unroll
  for (int s = 0; s < 4; s++) { A[4 * s + 3] = A[4 * s] ^ zz; if (s < 3) A[4 * s + 6] = A[4 * s + 1] ^ zz; }
}
template <int N, int H> __device__ __forceinline__ void conv_grp(float* T, const uint32_t* A, uint64_t dX) {
  WG_FENCE();
#pragma unroll
  for (int s = 0; s < 4; s++) wgmma_rs<N>(T, A + 4 * s, dX - (4 * H + s), (H > 0 || s > 0));
  WG_COMMIT();
}

__global__ void __launch_bounds__(384, 1) fused_kernel(const __grid_constant__ Maps maps, const Ptrs P, const uint32_t zz) {
  extern __shared__ __align__(1024) uint8_t smem[];
  const uint32_t sb = smem_u32(smem);
  const int tid = threadIdx.x;
  const int wg = __shfl_sync(0xffffffffu, tid >> 7, 0);
  const int b = blockIdx.x;
  const uint32_t bars = sb + SM_BAR;
  volatile uint32_t* s_target = (volatile uint32_t*)(smem + SM_BAR + 400);
#define BAR(i) (bars + 8u * (i))
  const int rt = b & 15, ct = b >> 4;
  const int rb = b & 31, cb = b >> 5;

  if (tid == 256) {
    if (sb & 1023) asm volatile("trap;");
    tmap_prefetch(&maps.x); tmap_prefetch(&maps.wg); tmap_prefetch(&maps.wu);
    for (int i = 0; i < 5; i++) { mbar_init(BAR(B_FW + i), 1); mbar_init(BAR(B_EW + i), 8); }
    for (int i = 0; i < 3; i++) { mbar_init(BAR(B_FX + i), 1); mbar_init(BAR(B_EX + i), 8); }
    for (int i = 0; i < 4; i++) { mbar_init(BAR(B_F2 + i), 1); mbar_init(BAR(B_E2 + i), 4); }
    mbar_init(BAR(B_KV), 1); mbar_init(BAR(B_XI), 1); mbar_init(BAR(B_HC), 96); mbar_init(BAR(B_Q), 1); mbar_init(BAR(B_Z), 1);
    for (int i = 0; i < 2; i++) { mbar_init(BAR(B_HS + i), 128); mbar_init(BAR(B_HF + i), 1); mbar_init(BAR(B_CD + i), 128); }
    mbar_init(BAR(B_GA), 128); mbar_init(BAR(B_PRE), 1); mbar_init(BAR(B_G1), 8);
    asm volatile("fence.mbarrier_init.release.cluster;" ::: "memory");
    asm volatile("fence.proxy.async;" ::: "memory");
    mbar_expect_tx(BAR(B_FX + 0), 16384); tma2d(sb + SM_X, &maps.x, BAR(B_FX + 0), 0, rt * 128);
    mbar_expect_tx(BAR(B_FW + 0), 24576); tma3d(sb + SM_W, &maps.wg, BAR(B_FW + 0), 0, 0, ct * 3);
    mbar_expect_tx(BAR(B_FW + 1), 24576); tma3d(sb + SM_W + 24576, &maps.wu, BAR(B_FW + 1), 0, 0, ct * 3);
  }
  __syncthreads();

  if (wg == 2) {
    asm volatile("setmaxnreg.dec.sync.aligned.u32 40;");
    const int warp = __shfl_sync(0xffffffffu, tid >> 5, 0) - 8, lane = tid & 31;
    if (warp == 0) {
      if (lane == 0) {
        for (int n = 2; n < 20; n++) {
          const int k = n < 16 ? (n >> 1) : 8 + (n & 1) ;
          const bool up = n < 16 ? (n & 1) : (n >= 18);
          if (!up) {
            const int xs = k % 3;
            if (k >= 3) mbar_wait(BAR(B_EX + xs), ((k / 3) - 1) & 1);
            mbar_expect_tx(BAR(B_FX + xs), 16384);
            tma2d(sb + SM_X + xs * 16384, &maps.x, BAR(B_FX + xs), k * 64, rt * 128);
          }
          const int s = n % 5;
          if (n >= 5) mbar_wait(BAR(B_EW + s), ((n / 5) - 1) & 1);
          mbar_expect_tx(BAR(B_FW + s), 24576);
          tma3d(sb + SM_W + s * 24576, up ? &maps.wu : &maps.wg, BAR(B_FW + s), 0, k * 64, ct * 3);
          if (n == 4) {
            mbar_expect_tx(BAR(B_KV), 42880);
            tma2d(sb + SM_D, &maps.k, BAR(B_KV), (b & 1) * 160, (b >> 1) * 32 - 3);
            tma2d(sb + SM_D + 22400, &maps.v, BAR(B_KV), (b & 1) * 160, (b >> 1) * 32);
          }
          if (n == 6) { l2_prefetch(P.ssm_k + (size_t)b * 5 * 2048, 20480); tmap_prefetch(&maps.wd); }
          if (n == 8) l2_prefetch(P.wd + (size_t)b * 12 * 640, 15360);
        }
        TS1(0);
        mbar_wait(BAR(B_PRE), 0);
        const uint32_t target = *s_target;
        mbar_wait(BAR(B_EW + 0), 1);
        flag_wait(&g_cnt[0], target);
        mbar_expect_tx(BAR(B_XI), 5 * XCH);
        bulk_g2s(sb + SM_W, g_X + (size_t)b * 5 * XCH, 5 * XCH, BAR(B_XI));
        TS1(1);
        mbar_wait(BAR(B_G1), 0);
        for (int s = 0; s < 4; s++) {
          mbar_expect_tx(BAR(B_F2 + s), 28672);
          tma3d(sb + SM_R2 + s * 28672 + 8192, &maps.wd, BAR(B_F2 + s), 0, s * 64, cb * 5);
        }
        TS1(2);
        flag_wait(&g_cnt[(1 + rb) * 32], target);
        TS1(3);
        const uint8_t* hsrc = g_h + (size_t)rb * 24 * 8192;
        for (int s = 0; s < 4; s++) bulk_g2s(sb + SM_R2 + s * 28672, hsrc + s * 8192, 8192, BAR(B_F2 + s));
        for (int c = 4; c < 24; c++) {
          const int s = c & 3;
          mbar_wait(BAR(B_E2 + s), ((c >> 2) - 1) & 1);
          mbar_expect_tx(BAR(B_F2 + s), 28672);
          bulk_g2s(sb + SM_R2 + s * 28672, hsrc + c * 8192, 8192, BAR(B_F2 + s));
          tma3d(sb + SM_R2 + s * 28672 + 8192, &maps.wd, BAR(B_F2 + s), 0, c * 64, cb * 5);
        }
        TS1(4);
      }
    } else {
      const int hw = warp - 1;
      {
        uint2 gw[5];
#pragma unroll
        for (int j = 0; j < 5; j++) gw[j] = __ldg((const uint2*)(P.gate_w + j * 128 + lane * 4));
        for (int r = hw; r < 16; r += 3) {
          const __nv_bfloat16* xr = P.x + (size_t)(b * 16 + r) * 640 + lane * 4;
          uint2 xv[5];
#pragma unroll
          for (int j = 0; j < 5; j++) xv[j] = __ldg((const uint2*)(xr + j * 128));
          float s = 0.f;
#pragma unroll
          for (int j = 0; j < 5; j++) {
            const uint32_t p0 = bmul2(xv[j].x, gw[j].x), p1 = bmul2(xv[j].y, gw[j].y);
            s += __uint_as_float(p0 << 16) + __uint_as_float(p0 & 0xffff0000u);
            s += __uint_as_float(p1 << 16) + __uint_as_float(p1 & 0xffff0000u);
          }
#pragma unroll
          for (int o = 16; o > 0; o >>= 1) s += __shfl_xor_sync(0xffffffffu, s, o);
          if (lane == 0) {
            const float l = __bfloat162float(__float2bfloat16_rn(s));
            g_gate[b * 16 + r] = __bfloat162float(__float2bfloat16_rn(1.0f / (1.0f + __expf(-l))));
          }
        }
      }
      mbar_wait(BAR(B_KV), 0);
      {
        const int rc = b >> 1, chb = (b & 1) * 320;
        for (int task = hw; task < 20; task += 3) {
          const int pg = task % 5, rq = task / 5;
          const int ch = chb + pg * 64 + lane * 2;
          const uint4 sk = __ldg((const uint4*)(P.shift_k + ch * 4));
          const uint32_t w0 = __byte_perm(sk.x, sk.z, 0x5410), w1 = __byte_perm(sk.x, sk.z, 0x7632);
          const uint32_t w2 = __byte_perm(sk.y, sk.w, 0x5410), w3 = __byte_perm(sk.y, sk.w, 0x7632);
          const uint32_t ka = sb + SM_D + rq * 8 * 640 + pg * 128 + lane * 4;
          uint32_t kk[11], o[8];
#pragma unroll
          for (int i = 0; i < 11; i++) kk[i] = lds32(ka + i * 640);
#pragma unroll
          for (int i = 0; i < 8; i++) {
            const uint32_t vv = lds32(ka + 22400 + i * 640);
            uint32_t a = bmul2(kk[i], w3);
            a = badd2(a, bmul2(kk[i + 1], w2));
            a = badd2(a, bmul2(kk[i + 2], w1));
            a = badd2(a, bmul2(kk[i + 3], w0));
            o[i] = bmul2(a, vv);
          }
          uint8_t* dst = g_X + (size_t)ch * XCH + (rq & 1) * XP + (12 + rc * 2 + (rq >> 1)) * 16;
          *(uint4*)dst = make_uint4(__byte_perm(o[1], o[0], 0x5410), __byte_perm(o[3], o[2], 0x5410), __byte_perm(o[5], o[4], 0x5410), __byte_perm(o[7], o[6], 0x5410));
          *(uint4*)(dst + XCH) = make_uint4(__byte_perm(o[1], o[0], 0x7632), __byte_perm(o[3], o[2], 0x7632), __byte_perm(o[5], o[4], 0x7632), __byte_perm(o[7], o[6], 0x7632));
        }
        const int ht = tid - 288;
        if (ht < 80) *(uint4*)(g_X + (size_t)(b * 5 + ht / 16) * XCH + ((ht >> 3) & 1) * XP + (4 + (ht & 7)) * 16) = make_uint4(0, 0, 0, 0);
      }
      bar_sync(3, 96);
      if (tid == 288) {
        asm volatile("fence.proxy.async;" ::: "memory");
        asm volatile("fence.acq_rel.gpu;" ::: "memory");
        uint32_t old;
        asm volatile("atom.relaxed.gpu.global.add.u32 %0, [%1], 1;" : "=r"(old) : "l"(&g_cnt[0]) : "memory");
        *s_target = (old & ~127u) + 128u;
        mbar_arrive(BAR(B_PRE));
        TS1(8);
      }
      {
        const int ht = tid - 288;
        const __nv_bfloat16* hk = P.ssm_k + (size_t)b * 5 * 2048;
        for (int i = ht; i < 1280; i += 96) {
          const int c = i >> 8, j = i & 255;
          const uint4 v = __ldg((const uint4*)(hk + i * 8));
          uint32_t prev = 0;
          if (j) prev = __ldg((const unsigned short*)(hk + i * 8 - 1));
          const uint32_t d = sb + SM_D + c * (2 * HC) + 32 + j * 16;
          sts128(d, v.x, v.y, v.z, v.w);
          sts128(d + HC, __byte_perm(prev, v.x, 0x5410), __byte_perm(v.x, v.y, 0x5432), __byte_perm(v.y, v.z, 0x5432), __byte_perm(v.z, v.w, 0x5432));
        }
        if (ht < 20) sts128(sb + SM_D + (ht >> 1) * HC + (ht & 1) * 16, 0, 0, 0, 0);
        mbar_arrive(BAR(B_HC));
      }
      if (hw < 2 && lane == 0) {
        mbar_wait(BAR(B_PRE), 0);
        const uint32_t target = *s_target;
        mbar_wait(BAR(B_HS + hw), 0);
        bulk_s2g(g_h + ((size_t)(rt * 2 + hw) * 24 + ct * 3) * 8192, sb + SM_W + (1 + hw) * 24576, 24576);
        asm volatile("cp.async.bulk.commit_group;" ::: "memory");
        asm volatile("cp.async.bulk.wait_group.read 0;" ::: "memory");
        mbar_arrive(BAR(B_HF + hw));
        asm volatile("cp.async.bulk.wait_group 0;" ::: "memory");
        flag_add(&g_cnt[(1 + rt * 2 + hw) * 32], 16);
        TS1(9 + hw);
        mbar_wait(BAR(B_CD + hw), 0);
        flag_add(&g_cnt[(33 + cb) * 32], 2);
        TS1(11 + hw);
        if (hw == 0) {
          mbar_expect_tx(BAR(B_Q), 20480);
          tma3d(sb + SM_W + 24576, &maps.q, BAR(B_Q), 0, rb * 64, cb * 5);
        } else {
          mbar_wait(BAR(B_CD + 0), 0);
          flag_wait(&g_cnt[(33 + cb) * 32], target);
          mbar_expect_tx(BAR(B_Z), 20480);
          tma2d(sb + SM_D, &maps.z, BAR(B_Z), rb * 64, cb * 160);
          TS1(13);
        }
      }
    }
  } else {
    asm volatile("setmaxnreg.inc.sync.aligned.u32 232;");
    const int t128 = tid & 127, w = __shfl_sync(0xffffffffu, t128 >> 5, 0), lane = tid & 31;
    {
      float ag[96], au[96];
#pragma unroll
      for (int i = 0; i < 96; i++) { ag[i] = 0.f; au[i] = 0.f; }
      const uint64_t dA0 = mkdesc(sb + SM_X + wg * 8192, 16, 1024, 1);
      const uint64_t dB0 = mkdesc(sb + SM_W, 8192, 1024, 1);
      uint32_t slot = 0, ph = 0, xs = 0, xph = 0, pslot = 0, pxs = 0;
#pragma unroll 1
      for (int k = 0; k < 8; k++) {
        mbar_wait(BAR(B_FX + xs), xph);
        const uint64_t dA = dA0 + xs * 1024;
        mbar_wait(BAR(B_FW + slot), ph);
        if (k == 0) TS(0);
        uint64_t dB = dB0 + slot * 1536;
        WG_FENCE();
#pragma unroll
        for (int kk = 0; kk < 4; kk++) wgmma_ss_tb_n192(ag, dA + kk * 2, dB + kk * 128, 1);
        WG_COMMIT();
        WG_WAIT(1);
        if (k > 0 && lane == 0) { mbar_arrive(BAR(B_EW + pslot)); mbar_arrive(BAR(B_EX + pxs)); }
        pslot = slot; if (++slot == 5) { slot = 0; ph ^= 1; }
        mbar_wait(BAR(B_FW + slot), ph);
        dB = dB0 + slot * 1536;
        WG_FENCE();
#pragma unroll
        for (int kk = 0; kk < 4; kk++) wgmma_ss_tb_n192(au, dA + kk * 2, dB + kk * 128, 1);
        WG_COMMIT();
        WG_WAIT(1);
        if (lane == 0) mbar_arrive(BAR(B_EW + pslot));
        pslot = slot; if (++slot == 5) { slot = 0; ph ^= 1; }
        pxs = xs; if (++xs == 3) { xs = 0; xph ^= 1; }
      }
      TS(1);
      mbar_wait(BAR(B_FX + 2), 0);
      mbar_wait(BAR(B_FW + 1), 1);
      WG_FENCE();
#pragma unroll
      for (int kk = 0; kk < 4; kk++) wgmma_ss_tb_n192(ag, dA0 + 2 * 1024 + kk * 2, dB0 + 1 * 1536 + kk * 128, 1);
      WG_COMMIT();
      WG_WAIT(1);
      if (lane == 0) mbar_arrive(BAR(B_EW + 0));
      mbar_wait(BAR(B_FX + 0), 1);
      mbar_wait(BAR(B_FW + 2), 1);
      WG_FENCE();
#pragma unroll
      for (int kk = 0; kk < 4; kk++) wgmma_ss_tb_n192(ag, dA0 + kk * 2, dB0 + 2 * 1536 + kk * 128, 1);
      WG_COMMIT();
      mbar_wait(BAR(B_FW + 3), 1);
      mbar_wait(BAR(B_FW + 4), 1);
      WG_FENCE();
#pragma unroll
      for (int kk = 0; kk < 4; kk++) wgmma_ss_tb_n192(au, dA0 + 2 * 1024 + kk * 2, dB0 + 3 * 1536 + kk * 128, 1);
#pragma unroll
      for (int kk = 0; kk < 4; kk++) wgmma_ss_tb_n192(au, dA0 + kk * 2, dB0 + 4 * 1536 + kk * 128, 1);
      WG_COMMIT();
      WG_WAIT(1);
      if (lane == 0) mbar_arrive(BAR(B_EW + 1));
      TS(2);
      uint32_t sg[48];
#pragma unroll
      for (int i = 0; i < 48; i++) sg[i] = pack_bf16(sigmoidf_fast(ag[2 * i]), sigmoidf_fast(ag[2 * i + 1]));
      TS(3);
      WG_WAIT(0);
      if (lane == 0) mbar_arrive(BAR(B_G1));
      TS(4);
      mbar_wait(BAR(B_EW + 1), 1);
      const int row = 16 * w + (lane & 7) + 8 * ((lane >> 3) & 1);
      const uint32_t hb = sb + SM_W + (1 + wg) * 24576 + row * 128;
#pragma unroll
      for (int j = 0; j < 24; j += 2) {
        uint32_t p[4];
#pragma unroll
        for (int e = 0; e < 4; e++) p[e] = bmul2(sg[2 * j + e], pack_bf16(au[4 * j + 2 * e], au[4 * j + 2 * e + 1]));
        const int cc = (j & 7) + (lane >> 4);
        stsm4(hb + (j >> 3) * 8192 + ((cc ^ (lane & 7)) << 4), p[0], p[1], p[2], p[3]);
      }
      asm volatile("fence.proxy.async.shared::cta;" ::: "memory");
      mbar_arrive(BAR(B_HS + wg));
      TS(5);
    }
    {
      const int g = lane >> 2, t = lane & 3;
      const uint32_t ra0 = sb + SM_D + 32 + ((g & 1) ? 2 * (128 * w + g - 2 * t - 9) : HC + 2 * (128 * w + g - 2 * t - 8));
      const uint32_t pbase = sb + SM_W + (1 + wg) * 24576;
      const uint32_t pa = pbase + w * (2 * PP) + ((lane >> 3) & 1) * PP + (8 * (lane >> 4) + (lane & 7) + 8 * w) * 16;
      mbar_wait(BAR(B_HC), 0);
      mbar_wait(BAR(B_XI), 0);
      const int c_beg = wg ? C0 : 0, c_end = wg ? 5 : C0;
#pragma unroll 1
      for (int c = c_beg; c < c_end; c++) {
        const uint32_t ra = ra0 + c * (2 * HC);
        const uint32_t xb = sb + SM_W + c * XCH;
        const uint64_t dX = mkdesc(xb + 192, XP, 128, 0);
        float T0[64], T1[48], T2[32], T3[16];
        uint32_t A0[16], A1[16], A2[16];
        conv_ldA<0>(A0, ra, zz); conv_ldA<128>(A1, ra, zz);
        conv_grp<128, 0>(T0, A0, dX); conv_ldA<1024>(A2, ra, zz);
        conv_grp<128, 1>(T0, A1, dX); WG_WAIT(1); conv_ldA<1024 + 128>(A0, ra, zz);
        conv_grp<96, 0>(T1, A2, dX); WG_WAIT(1); conv_ldA<2048>(A1, ra, zz);
        conv_grp<96, 1>(T1, A0, dX); WG_WAIT(1); conv_ldA<2048 + 128>(A2, ra, zz);
        conv_grp<64, 0>(T2, A1, dX); WG_WAIT(1); conv_ldA<3072>(A0, ra, zz);
        conv_grp<64, 1>(T2, A2, dX);
#pragma unroll
        for (int i = 0; i < 48; i++) T0[16 + i] += T1[i];
        WG_WAIT(1); conv_ldA<3072 + 128>(A1, ra, zz);
        conv_grp<32, 0>(T3, A0, dX);
        conv_grp<32, 1>(T3, A1, dX);
        const int ch = b * 5 + c;
        const uint32_t dv = __ldg((const unsigned short*)(P.ssm_D + ch));
        const uint32_t D2 = dv | (dv << 16);
        if (c == c_beg) mbar_wait(BAR(B_HF + wg), 0);
        WG_WAIT(0);
#pragma unroll
        for (int i = 0; i < 16; i++) T2[16 + i] += T3[i];
#pragma unroll
        for (int i = 0; i < 32; i++) T0[32 + i] += T2[i];
        bar_sync(1 + wg, 128);
#pragma unroll
        for (int j = 0; j < 16; j += 2)
          stsm4t(pa + j * 128, pack_bf16(T0[4 * j], T0[4 * j + 1]), pack_bf16(T0[4 * j + 2], T0[4 * j + 3]), pack_bf16(T0[4 * j + 4], T0[4 * j + 5]), pack_bf16(T0[4 * j + 6], T0[4 * j + 7]));
        bar_sync(1 + wg, 128);
#pragma unroll
        for (int cc = 0; cc < 2; cc++) {
          const int a = cc * 64 + (t128 >> 1), half = t128 & 1;
          float y[8];
#pragma unroll
          for (int q = 0; q < 4; q++) {
            uint4 v = make_uint4(0, 0, 0, 0);
            if (cc == 1 || a >= 8 * q) v = lds128(pbase + q * (2 * PP) + half * PP + a * 16);
            const uint32_t u[4] = {v.x, v.y, v.z, v.w};
#pragma unroll
            for (int e = 0; e < 4; e++) {
              const float lo = __uint_as_float(u[e] << 16), hi = __uint_as_float(u[e] & 0xffff0000u);
              if (q == 0) { y[2 * e] = lo; y[2 * e + 1] = hi; } else { y[2 * e] += lo; y[2 * e + 1] += hi; }
            }
          }
          const uint4 xv = lds128(xb + half * XP + (a + 12) * 16);
          const uint32_t xu[4] = {xv.x, xv.y, xv.z, xv.w};
          uint32_t o[4];
#pragma unroll
          for (int e = 0; e < 4; e++) o[e] = badd2(pack_bf16(y[2 * e], y[2 * e + 1]), bmul2(__byte_perm(xu[e], 0, 0x1032), D2));
          *(uint4*)(g_zT + (size_t)ch * 2048 + a * 16 + half * 8) = make_uint4(o[0], o[1], o[2], o[3]);
        }
        TS(6 + c - c_beg);
      }
      mbar_arrive(BAR(B_CD + wg));
    }
    const int g = lane >> 2;
    const float gv0 = __ldcg(&g_gate[rb * 64 + 16 * w + g]), gv1 = __ldcg(&g_gate[rb * 64 + 16 * w + g + 8]);
    const int frow = 16 * w + (lane & 7) + 8 * ((lane >> 3) & 1);
    const uint32_t fa = sb + SM_W + 24576 + frow * 64;
    const uint32_t fsw = (frow >> 1) & 3;
    if (wg == 0) {
      float acc[80];
#pragma unroll
      for (int i = 0; i < 80; i++) acc[i] = 0.f;
      const uint64_t dA0 = mkdesc(sb + SM_R2, 16, 1024, 1);
      const uint64_t dB0 = mkdesc(sb + SM_R2 + 8192, 4096, 512, 2);
#pragma unroll 1
      for (int c = 0; c < 24; c++) {
        const int s = c & 3;
        mbar_wait(BAR(B_F2 + s), (c >> 2) & 1);
        if (c == 0) TS(10);
        WG_FENCE();
#pragma unroll
        for (int kk = 0; kk < 4; kk++) wgmma_ss_tb_n160(acc, dA0 + s * 1792 + kk * 2, dB0 + s * 1792 + kk * 64, 1);
        WG_COMMIT();
        WG_WAIT(1);
        if (c > 0 && lane == 0) mbar_arrive(BAR(B_E2 + ((c - 1) & 3)));
      }
      TS(11);
      const uint32_t om0 = pack_bf16(1.0f - gv0, 1.0f - gv0), om1 = pack_bf16(1.0f - gv1, 1.0f - gv1);
      mbar_wait(BAR(B_GA), 0);
      uint4 ga[10];
#pragma unroll
      for (int j = 0; j < 10; j++) ga[j] = lds128(sb + SM_W + 2 * 24576 + j * 2048 + t128 * 16);
      WG_WAIT(0);
      TS(12);
#pragma unroll
      for (int j = 0; j < 10; j++) {
        const uint32_t o0 = badd2(ga[j].x, bmul2(om0, pack_bf16(acc[8 * j + 0], acc[8 * j + 1])));
        const uint32_t o1 = badd2(ga[j].y, bmul2(om1, pack_bf16(acc[8 * j + 2], acc[8 * j + 3])));
        const uint32_t o2 = badd2(ga[j].z, bmul2(om0, pack_bf16(acc[8 * j + 4], acc[8 * j + 5])));
        const uint32_t o3 = badd2(ga[j].w, bmul2(om1, pack_bf16(acc[8 * j + 6], acc[8 * j + 7])));
        const uint32_t cc = 2 * (j & 1) + (lane >> 4);
        stsm4(fa + (j >> 1) * 4096 + ((cc ^ fsw) << 4), o0, o1, o2, o3);
      }
      asm volatile("fence.proxy.async.shared::cta;" ::: "memory");
      bar_sync(1, 128);
      if (t128 == 0) {
        tma3d_store(&maps.o, sb + SM_W + 24576, 0, rb * 64, cb * 5);
        asm volatile("cp.async.bulk.commit_group;" ::: "memory");
        asm volatile("cp.async.bulk.wait_group.read 0;" ::: "memory");
      }
      TS(13);
    } else {
      const uint32_t g0 = pack_bf16(gv0, gv0), g1 = pack_bf16(gv1, gv1);
      const uint32_t za = sb + SM_D + ((lane & 7) + 8 * (lane >> 4)) * 128 + (((2 * w + ((lane >> 3) & 1)) ^ (lane & 7)) << 4);
      bar_sync(2, 128);
      mbar_wait(BAR(B_Q), 0);
      mbar_wait(BAR(B_Z), 0);
      TS(10);
#pragma unroll
      for (int j = 0; j < 10; j++) {
        const uint4 z = ldsm4t(za + j * 2048);
        const uint32_t cc = 2 * (j & 1) + (lane >> 4);
        const uint4 q = ldsm4(fa + (j >> 1) * 4096 + ((cc ^ fsw) << 4));
        sts128(sb + SM_W + 2 * 24576 + j * 2048 + t128 * 16, bmul2(g0, bmul2(q.x, z.x)), bmul2(g1, bmul2(q.y, z.y)), bmul2(g0, bmul2(q.z, z.z)), bmul2(g1, bmul2(q.w, z.w)));
      }
      mbar_arrive(BAR(B_GA));
      TS(11);
    }
  }
}

typedef CUresult (*EncFn)(CUtensorMap*, CUtensorMapDataType, cuuint32_t, void*, const cuuint64_t*, const cuuint64_t*, const cuuint32_t*, const cuuint32_t*,
                          CUtensorMapInterleave, CUtensorMapSwizzle, CUtensorMapL2promotion, CUtensorMapFloatOOBfill);

void enc(EncFn fn, CUtensorMap* m, CUtensorMapDataType dt, int rank, const void* p, const cuuint64_t* gd, const cuuint64_t* gs, const cuuint32_t* bd, CUtensorMapSwizzle sw) {
  cuuint32_t es[3] = {1, 1, 1};
  fn(m, dt, rank, (void*)p, gd, gs, bd, es, CU_TENSOR_MAP_INTERLEAVE_NONE, sw, CU_TENSOR_MAP_L2_PROMOTION_L2_128B, CU_TENSOR_MAP_FLOAT_OOB_FILL_NONE);
}

}

extern "C" void kernel_launch(void* const* d_in, const int* in_sizes, int n_in, void* d_out, int out_size) {
  static EncFn fn = nullptr;
  static void* zT = nullptr;
  if (!fn) {
    void* f = nullptr; cudaDriverEntryPointQueryResult qr;
    cudaGetDriverEntryPoint("cuTensorMapEncodeTiled", &f, cudaEnableDefault, &qr);
    fn = (EncFn)f;
    cudaGetSymbolAddress(&zT, g_zT);
    cudaFuncSetAttribute(fused_kernel, cudaFuncAttributeMaxDynamicSharedMemorySize, SM_TOTAL);
  }
  Maps m;
  const CUtensorMapDataType BF = CU_TENSOR_MAP_DATA_TYPE_BFLOAT16;
  { cuuint64_t gd[2] = {640, 2048}, gs[1] = {1280}; cuuint32_t bd[2] = {64, 128}; enc(fn, &m.x, BF, 2, d_in[0], gd, gs, bd, CU_TENSOR_MAP_SWIZZLE_128B); }
  { cuuint64_t gd[3] = {64, 640, 24}, gs[2] = {3072, 128}; cuuint32_t bd[3] = {64, 64, 3};
    enc(fn, &m.wg, BF, 3, d_in[7], gd, gs, bd, CU_TENSOR_MAP_SWIZZLE_128B); enc(fn, &m.wu, BF, 3, d_in[8], gd, gs, bd, CU_TENSOR_MAP_SWIZZLE_128B); }
  { cuuint64_t gd[3] = {32, 1536, 20}, gs[2] = {1280, 64}; cuuint32_t bd[3] = {32, 64, 5}; enc(fn, &m.wd, BF, 3, d_in[9], gd, gs, bd, CU_TENSOR_MAP_SWIZZLE_64B); }
  { cuuint64_t gd[2] = {320, 2048}, gs[1] = {1280}; cuuint32_t bk[2] = {160, 35}, bv[2] = {160, 32};
    enc(fn, &m.k, CU_TENSOR_MAP_DATA_TYPE_UINT32, 2, d_in[1], gd, gs, bk, CU_TENSOR_MAP_SWIZZLE_NONE);
    enc(fn, &m.v, CU_TENSOR_MAP_DATA_TYPE_UINT32, 2, d_in[2], gd, gs, bv, CU_TENSOR_MAP_SWIZZLE_NONE); }
  { cuuint64_t gd[3] = {32, 2048, 20}, gs[2] = {1280, 64}; cuuint32_t bd[3] = {32, 64, 5};
    enc(fn, &m.q, BF, 3, d_in[0], gd, gs, bd, CU_TENSOR_MAP_SWIZZLE_64B); enc(fn, &m.o, BF, 3, d_out, gd, gs, bd, CU_TENSOR_MAP_SWIZZLE_64B); }
  { cuuint64_t gd[2] = {2048, 640}, gs[1] = {4096}; cuuint32_t bd[2] = {64, 160}; enc(fn, &m.z, BF, 2, zT, gd, gs, bd, CU_TENSOR_MAP_SWIZZLE_128B); }
  Ptrs p;
  p.x = (const __nv_bfloat16*)d_in[0]; p.shift_k = (const __nv_bfloat16*)d_in[3]; p.ssm_k = (const __nv_bfloat16*)d_in[4];
  p.ssm_D = (const __nv_bfloat16*)d_in[5]; p.gate_w = (const __nv_bfloat16*)d_in[10]; p.wd = (const __nv_bfloat16*)d_in[9];
  fused_kernel<<<128, 384, SM_TOTAL, cudaStreamPerThread>>>(m, p, 0u);
}
```

```cpp
#include <cuda_runtime.h>
#include <cuda_bf16.h>
#include <cuda.h>
#include <stdint.h>

namespace {

constexpr int XP = 2240;
constexpr int XCH = 2 * XP;
constexpr int PP = 2496;
constexpr int TP = 8320;
#define KV0 3
#define KV1 4
#define KV2 6
#define KV3 8
#define WD_N 10
#define SK_N 99
#define C0 2
#define SG0 12
#define SG1 4
#define TSCH 1
#define TOK 5

constexpr uint32_t SM_W = 0;
constexpr uint32_t SM_X = 122880;
constexpr uint32_t SM_R2 = 73728;
constexpr uint32_t SM_D = 188416;
constexpr uint32_t SM_BAR = 231296;
constexpr uint32_t SM_GAP = 172032;
constexpr uint32_t SM_GT = SM_BAR + 512;
constexpr uint32_t SM_TOTAL = SM_GT + 256;
enum { B_FW = 0, B_EW = 5, B_FX = 10, B_EX = 13, B_HR = 16, B_XI = 17, B_HC = 18, B_F2 = 19  , B_E2 = 24  , B_Q = 29, B_WD = 30,
       B_HS = 31  , B_HF = 33  , B_CD = 35, B_PRE = 36, B_G1 = 37, B_KV = 38  , B_N = 42 };

__device__ __align__(1024) uint8_t g_X[640 * XCH];
__device__ __align__(1024) uint8_t g_h[2048 * 1536 * 2];
__device__ __align__(1024) uint8_t g_wd[1536 * 640 * 2];
__device__ __align__(1024) uint8_t g_z[640 * 4096];
__device__ __align__(1024) float g_gate[2048];
__device__ uint32_t g_cnt[40 * 32];
#define TS(i)
#define TS1(i)
#define TR(v)
#define TW(i, v)

struct Maps { CUtensorMap x, wg, wu, wd, k3, k8, v8, q, o, z; };
struct Ptrs { const __nv_bfloat16 *x, *shift_k, *ssm_k, *ssm_D, *gate_w; };

__device__ __forceinline__ uint32_t smem_u32(const void* p) { return (uint32_t)__cvta_generic_to_shared(p); }
__device__ __forceinline__ void mbar_init(uint32_t bar, uint32_t cnt) { asm volatile("mbarrier.init.shared::cta.b64 [%0], %1;" ::"r"(bar), "r"(cnt)); }
__device__ __forceinline__ void mbar_expect_tx(uint32_t bar, uint32_t bytes) { asm volatile("mbarrier.arrive.expect_tx.shared::cta.b64 _, [%0], %1;" ::"r"(bar), "r"(bytes) : "memory"); }
__device__ __forceinline__ void mbar_arrive(uint32_t bar) { asm volatile("mbarrier.arrive.shared::cta.b64 _, [%0];" ::"r"(bar) : "memory"); }
__device__ __forceinline__ void mbar_wait(uint32_t bar, uint32_t parity) {
  uint32_t ok;
  asm volatile("{.reg .pred p; mbarrier.try_wait.parity.shared::cta.b64 p, [%1], %2; selp.u32 %0,1,0,p;}" : "=r"(ok) : "r"(bar), "r"(parity) : "memory");
  if (!ok) {
    uint32_t it = 0;
    do {
      asm volatile("{.reg .pred p; mbarrier.try_wait.parity.shared::cta.b64 p, [%1], %2, 2000; selp.u32 %0,1,0,p;}" : "=r"(ok) : "r"(bar), "r"(parity) : "memory");
    } while (!ok && ++it < 100000u);
  }
}
__device__ __forceinline__ void flag_wait(const uint32_t* p, uint32_t target) {
  uint32_t v, it = 0;
  while (true) {
    asm volatile("ld.acquire.gpu.global.u32 %0, [%1];" : "=r"(v) : "l"(p) : "memory");
    if ((int)(v - target) >= 0) break;
    if (++it > 400000u) break;
    __nanosleep(20);
  }
  asm volatile("fence.proxy.async.global;" ::: "memory");
}
__device__ __forceinline__ void flag_add(uint32_t* p, uint32_t v) {
  asm volatile("red.release.gpu.global.add.u32 [%0], %1;" ::"l"(p), "r"(v) : "memory");
}
__device__ __forceinline__ void flag_add_relaxed(uint32_t* p, uint32_t v) {
  asm volatile("red.relaxed.gpu.global.add.u32 [%0], %1;" ::"l"(p), "r"(v) : "memory");
}
__device__ __forceinline__ bool mbar_test(uint32_t bar, uint32_t parity) {
  uint32_t ok;
  asm volatile("{.reg .pred p; mbarrier.test_wait.parity.shared::cta.b64 p, [%1], %2; selp.u32 %0,1,0,p;}" : "=r"(ok) : "r"(bar), "r"(parity) : "memory");
  return ok;
}
__device__ __forceinline__ void cp_async16(uint32_t dst, const void* src) { asm volatile("cp.async.cg.shared.global [%0], [%1], 16;" ::"r"(dst), "l"(src) : "memory"); }
__device__ __forceinline__ void tma2d(uint32_t dst, const CUtensorMap* m, uint32_t bar, int c0, int c1) {
  asm volatile("cp.async.bulk.tensor.2d.shared::cluster.global.mbarrier::complete_tx::bytes [%0], [%1, {%3,%4}], [%2];" ::"r"(dst), "l"(m), "r"(bar), "r"(c0), "r"(c1) : "memory");
}
__device__ __forceinline__ void tma3d(uint32_t dst, const CUtensorMap* m, uint32_t bar, int c0, int c1, int c2) {
  asm volatile("cp.async.bulk.tensor.3d.shared::cluster.global.mbarrier::complete_tx::bytes [%0], [%1, {%3,%4,%5}], [%2];" ::"r"(dst), "l"(m), "r"(bar), "r"(c0), "r"(c1), "r"(c2) : "memory");
}
__device__ __forceinline__ void tma3d_store(const CUtensorMap* m, uint32_t src, int c0, int c1, int c2) {
  asm volatile("cp.async.bulk.tensor.3d.global.shared::cta.bulk_group [%0, {%2,%3,%4}], [%1];" ::"l"(m), "r"(src), "r"(c0), "r"(c1), "r"(c2) : "memory");
}
__device__ __forceinline__ void bulk_g2s(uint32_t dst, const void* src, uint32_t bytes, uint32_t bar) {
  asm volatile("cp.async.bulk.shared::cluster.global.mbarrier::complete_tx::bytes [%0], [%1], %2, [%3];" ::"r"(dst), "l"(src), "r"(bytes), "r"(bar) : "memory");
}
__device__ __forceinline__ void bulk_s2g(void* dst, uint32_t src, uint32_t bytes) {
  asm volatile("cp.async.bulk.global.shared::cta.bulk_group [%0], [%1], %2;" ::"l"(dst), "r"(src), "r"(bytes) : "memory");
}
__device__ __forceinline__ void l2_prefetch(const void* src, uint32_t bytes) {
  asm volatile("cp.async.bulk.prefetch.L2.global [%0], %1;" ::"l"(src), "r"(bytes) : "memory");
}
__device__ __forceinline__ void tmap_prefetch(const CUtensorMap* m) { asm volatile("prefetch.tensormap [%0];" ::"l"(m) : "memory"); }
__device__ __forceinline__ uint64_t mkdesc(uint32_t addr, uint32_t lbo, uint32_t sbo, uint32_t swz) {
  return (uint64_t)((addr & 0x3FFFF) >> 4) | ((uint64_t)(lbo >> 4) << 16) | ((uint64_t)(sbo >> 4) << 32) | ((uint64_t)swz << 62);
}
#define WG_FENCE() asm volatile("wgmma.fence.sync.aligned;" ::: "memory")
#define WG_COMMIT() asm volatile("wgmma.commit_group.sync.aligned;" ::: "memory")
#define WG_WAIT(n) asm volatile("wgmma.wait_group.sync.aligned " #n ";" ::: "memory")
__device__ __forceinline__ void bar_sync(int id, int n) { asm volatile("bar.sync %0, %1;" ::"r"(id), "r"(n) : "memory"); }
__device__ __forceinline__ void bar_arrive(int id, int n) { asm volatile("bar.arrive %0, %1;" ::"r"(id), "r"(n) : "memory"); }
__device__ __forceinline__ uint32_t pack_bf16(float lo, float hi) { uint32_t r; asm("cvt.rn.bf16x2.f32 %0, %1, %2;" : "=r"(r) : "f"(hi), "f"(lo)); return r; }
__device__ __forceinline__ uint32_t bmul2(uint32_t a, uint32_t b) { uint32_t r; asm("mul.rn.bf16x2 %0, %1, %2;" : "=r"(r) : "r"(a), "r"(b)); return r; }
__device__ __forceinline__ uint32_t badd2(uint32_t a, uint32_t b) { uint32_t r; asm("add.rn.bf16x2 %0, %1, %2;" : "=r"(r) : "r"(a), "r"(b)); return r; }
__device__ __forceinline__ uint32_t bfma2(uint32_t a, uint32_t b, uint32_t c) { uint32_t r; asm("fma.rn.bf16x2 %0, %1, %2, %3;" : "=r"(r) : "r"(a), "r"(b), "r"(c)); return r; }
__device__ __forceinline__ uint32_t lds32(uint32_t a) { uint32_t r; asm volatile("ld.shared.u32 %0, [%1];" : "=r"(r) : "r"(a)); return r; }
__device__ __forceinline__ uint4 lds128(uint32_t a) { uint4 v; asm volatile("ld.shared.v4.u32 {%0,%1,%2,%3}, [%4];" : "=r"(v.x), "=r"(v.y), "=r"(v.z), "=r"(v.w) : "r"(a)); return v; }
__device__ __forceinline__ void sts128(uint32_t a, uint32_t x, uint32_t y, uint32_t z, uint32_t w) { asm volatile("st.shared.v4.u32 [%0], {%1,%2,%3,%4};" ::"r"(a), "r"(x), "r"(y), "r"(z), "r"(w) : "memory"); }
__device__ __forceinline__ void stsm4(uint32_t a, uint32_t x, uint32_t y, uint32_t z, uint32_t w) { asm volatile("stmatrix.sync.aligned.m8n8.x4.shared.b16 [%0], {%1,%2,%3,%4};" ::"r"(a), "r"(x), "r"(y), "r"(z), "r"(w) : "memory"); }
__device__ __forceinline__ void stsm4t(uint32_t a, uint32_t x, uint32_t y, uint32_t z, uint32_t w) { asm volatile("stmatrix.sync.aligned.m8n8.x4.trans.shared.b16 [%0], {%1,%2,%3,%4};" ::"r"(a), "r"(x), "r"(y), "r"(z), "r"(w) : "memory"); }
__device__ __forceinline__ uint4 ldsm4(uint32_t a) { uint4 v; asm volatile("ldmatrix.sync.aligned.m8n8.x4.shared.b16 {%0,%1,%2,%3}, [%4];" : "=r"(v.x), "=r"(v.y), "=r"(v.z), "=r"(v.w) : "r"(a) : "memory"); return v; }
__device__ __forceinline__ uint4 ldsm4t(uint32_t a) { uint4 v; asm volatile("ldmatrix.sync.aligned.m8n8.x4.trans.shared.b16 {%0,%1,%2,%3}, [%4];" : "=r"(v.x), "=r"(v.y), "=r"(v.z), "=r"(v.w) : "r"(a) : "memory"); return v; }
__device__ __forceinline__ float sigmoidf_fast(float x) {
  float t;
  asm volatile("tanh.approx.f32 %0, %1;" : "=f"(t) : "f"(x * 0.5f));
  return fmaf(t, 0.5f, 0.5f);
}
__device__ __forceinline__ void fadd_v(float& a, float b) { asm volatile("add.f32 %0, %0, %1;" : "+f"(a) : "f"(b)); }

__device__ __forceinline__ void wgmma_ss_tb_n192(float* d, uint64_t da, uint64_t db, int sc) {
  asm volatile("{.reg .pred p; setp.ne.b32 p, %98, 0;\n"
   "wgmma.mma_async.sync.aligned.m64n192k16.f32.bf16.bf16 {%0,%1,%2,%3,%4,%5,%6,%7,%8,%9,%10,%11,%12,%13,%14,%15,%16,%17,%18,%19,%20,%21,%22,%23,%24,%25,%26,%27,%28,%29,%30,%31,%32,%33,%34,%35,%36,%37,%38,%39,%40,%41,%42,%43,%44,%45,%46,%47,%48,%49,%50,%51,%52,%53,%54,%55,%56,%57,%58,%59,%60,%61,%62,%63,%64,%65,%66,%67,%68,%69,%70,%71,%72,%73,%74,%75,%76,%77,%78,%79,%80,%81,%82,%83,%84,%85,%86,%87,%88,%89,%90,%91,%92,%93,%94,%95}, %96, %97, p, 1, 1, 0, 1;}\n"
   : "+f"(d[0]),"+f"(d[1]),"+f"(d[2]),"+f"(d[3]),"+f"(d[4]),"+f"(d[5]),"+f"(d[6]),"+f"(d[7]),"+f"(d[8]),"+f"(d[9]),"+f"(d[10]),"+f"(d[11]),"+f"(d[12]),"+f"(d[13]),"+f"(d[14]),"+f"(d[15]),"+f"(d[16]),"+f"(d[17]),"+f"(d[18]),"+f"(d[19]),"+f"(d[20]),"+f"(d[21]),"+f"(d[22]),"+f"(d[23]),"+f"(d[24]),"+f"(d[25]),"+f"(d[26]),"+f"(d[27]),"+f"(d[28]),"+f"(d[29]),"+f"(d[30]),"+f"(d[31]),"+f"(d[32]),"+f"(d[33]),"+f"(d[34]),"+f"(d[35]),"+f"(d[36]),"+f"(d[37]),"+f"(d[38]),"+f"(d[39]),"+f"(d[40]),"+f"(d[41]),"+f"(d[42]),"+f"(d[43]),"+f"(d[44]),"+f"(d[45]),"+f"(d[46]),"+f"(d[47]),"+f"(d[48]),"+f"(d[49]),"+f"(d[50]),"+f"(d[51]),"+f"(d[52]),"+f"(d[53]),"+f"(d[54]),"+f"(d[55]),"+f"(d[56]),"+f"(d[57]),"+f"(d[58]),"+f"(d[59]),"+f"(d[60]),"+f"(d[61]),"+f"(d[62]),"+f"(d[63]),"+f"(d[64]),"+f"(d[65]),"+f"(d[66]),"+f"(d[67]),"+f"(d[68]),"+f"(d[69]),"+f"(d[70]),"+f"(d[71]),"+f"(d[72]),"+f"(d[73]),"+f"(d[74]),"+f"(d[75]),"+f"(d[76]),"+f"(d[77]),"+f"(d[78]),"+f"(d[79]),"+f"(d[80]),"+f"(d[81]),"+f"(d[82]),"+f"(d[83]),"+f"(d[84]),"+f"(d[85]),"+f"(d[86]),"+f"(d[87]),"+f"(d[88]),"+f"(d[89]),"+f"(d[90]),"+f"(d[91]),"+f"(d[92]),"+f"(d[93]),"+f"(d[94]),"+f"(d[95]) : "l"(da), "l"(db), "r"(sc));
}
__device__ __forceinline__ void wgmma_ss_tb_n160(float* d, uint64_t da, uint64_t db, int sc) {
  asm volatile("{.reg .pred p; setp.ne.b32 p, %82, 0;\n"
   "wgmma.mma_async.sync.aligned.m64n160k16.f32.bf16.bf16 {%0,%1,%2,%3,%4,%5,%6,%7,%8,%9,%10,%11,%12,%13,%14,%15,%16,%17,%18,%19,%20,%21,%22,%23,%24,%25,%26,%27,%28,%29,%30,%31,%32,%33,%34,%35,%36,%37,%38,%39,%40,%41,%42,%43,%44,%45,%46,%47,%48,%49,%50,%51,%52,%53,%54,%55,%56,%57,%58,%59,%60,%61,%62,%63,%64,%65,%66,%67,%68,%69,%70,%71,%72,%73,%74,%75,%76,%77,%78,%79}, %80, %81, p, 1, 1, 0, 1;}\n"
   : "+f"(d[0]),"+f"(d[1]),"+f"(d[2]),"+f"(d[3]),"+f"(d[4]),"+f"(d[5]),"+f"(d[6]),"+f"(d[7]),"+f"(d[8]),"+f"(d[9]),"+f"(d[10]),"+f"(d[11]),"+f"(d[12]),"+f"(d[13]),"+f"(d[14]),"+f"(d[15]),"+f"(d[16]),"+f"(d[17]),"+f"(d[18]),"+f"(d[19]),"+f"(d[20]),"+f"(d[21]),"+f"(d[22]),"+f"(d[23]),"+f"(d[24]),"+f"(d[25]),"+f"(d[26]),"+f"(d[27]),"+f"(d[28]),"+f"(d[29]),"+f"(d[30]),"+f"(d[31]),"+f"(d[32]),"+f"(d[33]),"+f"(d[34]),"+f"(d[35]),"+f"(d[36]),"+f"(d[37]),"+f"(d[38]),"+f"(d[39]),"+f"(d[40]),"+f"(d[41]),"+f"(d[42]),"+f"(d[43]),"+f"(d[44]),"+f"(d[45]),"+f"(d[46]),"+f"(d[47]),"+f"(d[48]),"+f"(d[49]),"+f"(d[50]),"+f"(d[51]),"+f"(d[52]),"+f"(d[53]),"+f"(d[54]),"+f"(d[55]),"+f"(d[56]),"+f"(d[57]),"+f"(d[58]),"+f"(d[59]),"+f"(d[60]),"+f"(d[61]),"+f"(d[62]),"+f"(d[63]),"+f"(d[64]),"+f"(d[65]),"+f"(d[66]),"+f"(d[67]),"+f"(d[68]),"+f"(d[69]),"+f"(d[70]),"+f"(d[71]),"+f"(d[72]),"+f"(d[73]),"+f"(d[74]),"+f"(d[75]),"+f"(d[76]),"+f"(d[77]),"+f"(d[78]),"+f"(d[79]) : "l"(da), "l"(db), "r"(sc));
}
__device__ __forceinline__ void wgmma_rs_tb_n192(float* d, const uint4& a, uint64_t db, int sc) {
  asm volatile("{.reg .pred p; setp.ne.b32 p, %101, 0;\n"
   "wgmma.mma_async.sync.aligned.m64n192k16.f32.bf16.bf16 {%0,%1,%2,%3,%4,%5,%6,%7,%8,%9,%10,%11,%12,%13,%14,%15,%16,%17,%18,%19,%20,%21,%22,%23,%24,%25,%26,%27,%28,%29,%30,%31,%32,%33,%34,%35,%36,%37,%38,%39,%40,%41,%42,%43,%44,%45,%46,%47,%48,%49,%50,%51,%52,%53,%54,%55,%56,%57,%58,%59,%60,%61,%62,%63,%64,%65,%66,%67,%68,%69,%70,%71,%72,%73,%74,%75,%76,%77,%78,%79,%80,%81,%82,%83,%84,%85,%86,%87,%88,%89,%90,%91,%92,%93,%94,%95}, {%96,%97,%98,%99}, %100, p, 1, 1, 1;}\n"
   : "+f"(d[0]),"+f"(d[1]),"+f"(d[2]),"+f"(d[3]),"+f"(d[4]),"+f"(d[5]),"+f"(d[6]),"+f"(d[7]),"+f"(d[8]),"+f"(d[9]),"+f"(d[10]),"+f"(d[11]),"+f"(d[12]),"+f"(d[13]),"+f"(d[14]),"+f"(d[15]),"+f"(d[16]),"+f"(d[17]),"+f"(d[18]),"+f"(d[19]),"+f"(d[20]),"+f"(d[21]),"+f"(d[22]),"+f"(d[23]),"+f"(d[24]),"+f"(d[25]),"+f"(d[26]),"+f"(d[27]),"+f"(d[28]),"+f"(d[29]),"+f"(d[30]),"+f"(d[31]),"+f"(d[32]),"+f"(d[33]),"+f"(d[34]),"+f"(d[35]),"+f"(d[36]),"+f"(d[37]),"+f"(d[38]),"+f"(d[39]),"+f"(d[40]),"+f"(d[41]),"+f"(d[42]),"+f"(d[43]),"+f"(d[44]),"+f"(d[45]),"+f"(d[46]),"+f"(d[47]),"+f"(d[48]),"+f"(d[49]),"+f"(d[50]),"+f"(d[51]),"+f"(d[52]),"+f"(d[53]),"+f"(d[54]),"+f"(d[55]),"+f"(d[56]),"+f"(d[57]),"+f"(d[58]),"+f"(d[59]),"+f"(d[60]),"+f"(d[61]),"+f"(d[62]),"+f"(d[63]),"+f"(d[64]),"+f"(d[65]),"+f"(d[66]),"+f"(d[67]),"+f"(d[68]),"+f"(d[69]),"+f"(d[70]),"+f"(d[71]),"+f"(d[72]),"+f"(d[73]),"+f"(d[74]),"+f"(d[75]),"+f"(d[76]),"+f"(d[77]),"+f"(d[78]),"+f"(d[79]),"+f"(d[80]),"+f"(d[81]),"+f"(d[82]),"+f"(d[83]),"+f"(d[84]),"+f"(d[85]),"+f"(d[86]),"+f"(d[87]),"+f"(d[88]),"+f"(d[89]),"+f"(d[90]),"+f"(d[91]),"+f"(d[92]),"+f"(d[93]),"+f"(d[94]),"+f"(d[95]) : "r"(a.x), "r"(a.y), "r"(a.z), "r"(a.w), "l"(db), "r"(sc));
}
template<int N> __device__ __forceinline__ void wgmma_rs(float* d, const uint32_t* a, uint64_t db, int sc);
template<> __device__ __forceinline__ void wgmma_rs<128>(float* d, const uint32_t* a, uint64_t db, int sc) {
  asm volatile("{.reg .pred p; setp.ne.b32 p, %69, 0;\n"
   "wgmma.mma_async.sync.aligned.m64n128k16.f32.bf16.bf16 {%0,%1,%2,%3,%4,%5,%6,%7,%8,%9,%10,%11,%12,%13,%14,%15,%16,%17,%18,%19,%20,%21,%22,%23,%24,%25,%26,%27,%28,%29,%30,%31,%32,%33,%34,%35,%36,%37,%38,%39,%40,%41,%42,%43,%44,%45,%46,%47,%48,%49,%50,%51,%52,%53,%54,%55,%56,%57,%58,%59,%60,%61,%62,%63}, {%64,%65,%66,%67}, %68, p, 1, 1, 0;}\n"
   : "+f"(d[0]),"+f"(d[1]),"+f"(d[2]),"+f"(d[3]),"+f"(d[4]),"+f"(d[5]),"+f"(d[6]),"+f"(d[7]),"+f"(d[8]),"+f"(d[9]),"+f"(d[10]),"+f"(d[11]),"+f"(d[12]),"+f"(d[13]),"+f"(d[14]),"+f"(d[15]),"+f"(d[16]),"+f"(d[17]),"+f"(d[18]),"+f"(d[19]),"+f"(d[20]),"+f"(d[21]),"+f"(d[22]),"+f"(d[23]),"+f"(d[24]),"+f"(d[25]),"+f"(d[26]),"+f"(d[27]),"+f"(d[28]),"+f"(d[29]),"+f"(d[30]),"+f"(d[31]),"+f"(d[32]),"+f"(d[33]),"+f"(d[34]),"+f"(d[35]),"+f"(d[36]),"+f"(d[37]),"+f"(d[38]),"+f"(d[39]),"+f"(d[40]),"+f"(d[41]),"+f"(d[42]),"+f"(d[43]),"+f"(d[44]),"+f"(d[45]),"+f"(d[46]),"+f"(d[47]),"+f"(d[48]),"+f"(d[49]),"+f"(d[50]),"+f"(d[51]),"+f"(d[52]),"+f"(d[53]),"+f"(d[54]),"+f"(d[55]),"+f"(d[56]),"+f"(d[57]),"+f"(d[58]),"+f"(d[59]),"+f"(d[60]),"+f"(d[61]),"+f"(d[62]),"+f"(d[63]) : "r"(a[0]), "r"(a[1]), "r"(a[2]), "r"(a[3]), "l"(db), "r"(sc));
}
template<> __device__ __forceinline__ void wgmma_rs<96>(float* d, const uint32_t* a, uint64_t db, int sc) {
  asm volatile("{.reg .pred p; setp.ne.b32 p, %53, 0;\n"
   "wgmma.mma_async.sync.aligned.m64n96k16.f32.bf16.bf16 {%0,%1,%2,%3,%4,%5,%6,%7,%8,%9,%10,%11,%12,%13,%14,%15,%16,%17,%18,%19,%20,%21,%22,%23,%24,%25,%26,%27,%28,%29,%30,%31,%32,%33,%34,%35,%36,%37,%38,%39,%40,%41,%42,%43,%44,%45,%46,%47}, {%48,%49,%50,%51}, %52, p, 1, 1, 0;}\n"
   : "+f"(d[0]),"+f"(d[1]),"+f"(d[2]),"+f"(d[3]),"+f"(d[4]),"+f"(d[5]),"+f"(d[6]),"+f"(d[7]),"+f"(d[8]),"+f"(d[9]),"+f"(d[10]),"+f"(d[11]),"+f"(d[12]),"+f"(d[13]),"+f"(d[14]),"+f"(d[15]),"+f"(d[16]),"+f"(d[17]),"+f"(d[18]),"+f"(d[19]),"+f"(d[20]),"+f"(d[21]),"+f"(d[22]),"+f"(d[23]),"+f"(d[24]),"+f"(d[25]),"+f"(d[26]),"+f"(d[27]),"+f"(d[28]),"+f"(d[29]),"+f"(d[30]),"+f"(d[31]),"+f"(d[32]),"+f"(d[33]),"+f"(d[34]),"+f"(d[35]),"+f"(d[36]),"+f"(d[37]),"+f"(d[38]),"+f"(d[39]),"+f"(d[40]),"+f"(d[41]),"+f"(d[42]),"+f"(d[43]),"+f"(d[44]),"+f"(d[45]),"+f"(d[46]),"+f"(d[47]) : "r"(a[0]), "r"(a[1]), "r"(a[2]), "r"(a[3]), "l"(db), "r"(sc));
}
template<> __device__ __forceinline__ void wgmma_rs<64>(float* d, const uint32_t* a, uint64_t db, int sc) {
  asm volatile("{.reg .pred p; setp.ne.b32 p, %37, 0;\n"
   "wgmma.mma_async.sync.aligned.m64n64k16.f32.bf16.bf16 {%0,%1,%2,%3,%4,%5,%6,%7,%8,%9,%10,%11,%12,%13,%14,%15,%16,%17,%18,%19,%20,%21,%22,%23,%24,%25,%26,%27,%28,%29,%30,%31}, {%32,%33,%34,%35}, %36, p, 1, 1, 0;}\n"
   : "+f"(d[0]),"+f"(d[1]),"+f"(d[2]),"+f"(d[3]),"+f"(d[4]),"+f"(d[5]),"+f"(d[6]),"+f"(d[7]),"+f"(d[8]),"+f"(d[9]),"+f"(d[10]),"+f"(d[11]),"+f"(d[12]),"+f"(d[13]),"+f"(d[14]),"+f"(d[15]),"+f"(d[16]),"+f"(d[17]),"+f"(d[18]),"+f"(d[19]),"+f"(d[20]),"+f"(d[21]),"+f"(d[22]),"+f"(d[23]),"+f"(d[24]),"+f"(d[25]),"+f"(d[26]),"+f"(d[27]),"+f"(d[28]),"+f"(d[29]),"+f"(d[30]),"+f"(d[31]) : "r"(a[0]), "r"(a[1]), "r"(a[2]), "r"(a[3]), "l"(db), "r"(sc));
}
template<> __device__ __forceinline__ void wgmma_rs<32>(float* d, const uint32_t* a, uint64_t db, int sc) {
  asm volatile("{.reg .pred p; setp.ne.b32 p, %21, 0;\n"
   "wgmma.mma_async.sync.aligned.m64n32k16.f32.bf16.bf16 {%0,%1,%2,%3,%4,%5,%6,%7,%8,%9,%10,%11,%12,%13,%14,%15}, {%16,%17,%18,%19}, %20, p, 1, 1, 0;}\n"
   : "+f"(d[0]),"+f"(d[1]),"+f"(d[2]),"+f"(d[3]),"+f"(d[4]),"+f"(d[5]),"+f"(d[6]),"+f"(d[7]),"+f"(d[8]),"+f"(d[9]),"+f"(d[10]),"+f"(d[11]),"+f"(d[12]),"+f"(d[13]),"+f"(d[14]),"+f"(d[15]) : "r"(a[0]), "r"(a[1]), "r"(a[2]), "r"(a[3]), "l"(db), "r"(sc));
}

__device__ __forceinline__ void conv_dupA(uint32_t* A, uint32_t zz) {
#pragma unroll
  for (int s = 0; s < 4; s++) {
    asm volatile("xor.b32 %0, %1, %2;" : "=r"(A[4 * s + 3]) : "r"(A[4 * s]), "r"(zz));
    if (s < 3) asm volatile("xor.b32 %0, %1, %2;" : "=r"(A[4 * s + 6]) : "r"(A[4 * s + 1]), "r"(zz));
  }
}
template <int OFF, int DUP = 1> __device__ __forceinline__ void conv_ldA(uint32_t* A, uint32_t ra, uint32_t zz) {
  A[2] = lds32(ra + OFF);
#pragma unroll
  for (int s = 0; s < 4; s++) { A[4 * s] = lds32(ra + OFF + 32 * s + 16); A[4 * s + 1] = lds32(ra + OFF + 32 * s + 32); }
  if (DUP) conv_dupA(A, zz);
}
template <int N, int H, int ACC = 0> __device__ __forceinline__ void conv_grp(float* T, const uint32_t* A, uint64_t dX) {
  WG_FENCE();
#pragma unroll
  for (int s = 0; s < 4; s++) wgmma_rs<N>(T, A + 4 * s, dX - (4 * H + s), (ACC || H > 0 || s > 0));
  WG_COMMIT();
}
template <int H> __device__ __forceinline__ void conv_grp2(float* T, float* U, const uint32_t* A, uint64_t dX) {
  WG_FENCE();
#pragma unroll
  for (int s = 0; s < 4; s++) {
    wgmma_rs<64>(T, A + 4 * s, dX + 32 - (4 * H + s), (H > 0 || s > 0));
    wgmma_rs<32>(U, A + 4 * s, dX - (4 * H + s), (H > 0 || s > 0));
  }
  WG_COMMIT();
}

__global__ void __launch_bounds__(384, 1) fused_kernel(const __grid_constant__ Maps maps, const Ptrs P, const uint32_t zz) {
  extern __shared__ __align__(1024) uint8_t smem[];
  const uint32_t sb = smem_u32(smem);
  const int tid = threadIdx.x;
  const int wg = __shfl_sync(0xffffffffu, tid >> 7, 0);
  const int b = blockIdx.x;
  const uint32_t bars = sb + SM_BAR;
  volatile uint32_t* s_target = (volatile uint32_t*)(smem + SM_BAR + 400);
#define BAR(i) (bars + 8u * (i))
  const int rt = b & 15, ct = b >> 4;
  const int rb = b & 31, cb = b >> 5;

  if (tid == 256) {
    if (sb & 1023) asm volatile("trap;");
    tmap_prefetch(&maps.x); tmap_prefetch(&maps.wg); tmap_prefetch(&maps.wu);
    for (int i = 0; i < 5; i++) { mbar_init(BAR(B_FW + i), 1); mbar_init(BAR(B_EW + i), 8); }
    for (int i = 0; i < 3; i++) { mbar_init(BAR(B_FX + i), 1); mbar_init(BAR(B_EX + i), 9); }
    for (int i = 0; i < 5; i++) { mbar_init(BAR(B_F2 + i), 1); mbar_init(BAR(B_E2 + i), 4); }
    for (int i = 0; i < 4; i++) mbar_init(BAR(B_KV + i), 1);
    mbar_init(BAR(B_WD), 1); mbar_init(BAR(B_XI), 1); mbar_init(BAR(B_HC), 1); mbar_init(BAR(B_HR), 1); mbar_init(BAR(B_Q), 2); mbar_init(BAR(B_CD), 128);
    for (int i = 0; i < 2; i++) { mbar_init(BAR(B_HS + i), 129); mbar_init(BAR(B_HF + i), 1); }
    mbar_init(BAR(B_PRE), 1); mbar_init(BAR(B_G1), 9);
    asm volatile("fence.proxy.async.shared::cta;" ::: "memory");
    mbar_expect_tx(BAR(B_FX + 0), 16384); tma2d(sb + SM_X, &maps.x, BAR(B_FX + 0), 0, rt * 128);
    mbar_expect_tx(BAR(B_FW + 0), 24576); tma3d(sb + SM_W, &maps.wg, BAR(B_FW + 0), 0, 0, ct * 3); tma3d(sb + SM_W + 12288, &maps.wu, BAR(B_FW + 0), 0, 0, ct * 3);
    mbar_expect_tx(BAR(B_FW + 1), 24576); tma3d(sb + SM_W + 24576, &maps.wg, BAR(B_FW + 1), 0, 32, ct * 3); tma3d(sb + SM_W + 24576 + 12288, &maps.wu, BAR(B_FW + 1), 0, 32, ct * 3);
  }
  __syncthreads();

  if (wg == 2) {
    asm volatile("setmaxnreg.dec.sync.aligned.u32 40;");
    const int warp = __shfl_sync(0xffffffffu, tid >> 5, 0) - 8, lane = tid & 31;
    if (warp == 0) {
      if (lane == 0) {
        for (int n = 2; n < 20; n++) {
          const int k = n < 14 ? (n >> 1) : n < 17 ? n - 7 : n - 10;
          const bool up = n < 14 ? (n & 1) : (n >= 17);
          if (!up) {
            const int xs = k % 3;
            if (k >= 3) mbar_wait(BAR(B_EX + xs), ((k / 3) - 1) & 1);
            mbar_expect_tx(BAR(B_FX + xs), 16384);
            tma2d(sb + SM_X + xs * 16384, &maps.x, BAR(B_FX + xs), k * 64, rt * 128);
          }
          const int s = n % 5;
          if (n >= 5) mbar_wait(BAR(B_EW + s), ((n / 5) - 1) & 1);
          mbar_expect_tx(BAR(B_FW + s), 24576);
          tma3d(sb + SM_W + s * 24576, n >= 17 ? &maps.wu : &maps.wg, BAR(B_FW + s), 0, n < 14 ? n * 32 : k * 64, ct * 3);
          tma3d(sb + SM_W + s * 24576 + 12288, n < 14 || n >= 17 ? &maps.wu : &maps.wg, BAR(B_FW + s), 0, n < 14 ? n * 32 : k * 64 + 32, ct * 3);
          if (n == KV0 || n == KV1 || n == KV2 || n == KV3) {
            const int r = n == KV0 ? 0 : n == KV1 ? 1 : n == KV2 ? 2 : 3;
            mbar_expect_tx(BAR(B_KV + r), r ? 10240 : 10240 + 1920);
            if (!r) tma2d(sb + SM_D, &maps.k3, BAR(B_KV), (b & 1) * 160, (b >> 1) * 32 - 3);
            tma2d(sb + SM_D + 1920 + r * 5120, &maps.k8, BAR(B_KV + r), (b & 1) * 160, (b >> 1) * 32 + r * 8);
            tma2d(sb + SM_D + 22400 + r * 5120, &maps.v8, BAR(B_KV + r), (b & 1) * 160, (b >> 1) * 32 + r * 8);
          }
          if (n == WD_N) {
            mbar_expect_tx(BAR(B_WD), b < 120 ? 16384 : 0);
            if (b < 120) tma3d(sb + SM_GAP, &maps.wd, BAR(B_WD), 0, (b / 5) * 64, (b % 5) * 4);
          }
          if (n == SK_N) l2_prefetch(P.ssm_k + (size_t)b * 5 * 2048, 20480);
        }
        TS1(0);
        mbar_wait(BAR(B_PRE), 0);
        const uint32_t target = *s_target;
        mbar_wait(BAR(B_EW + 0), 1);
        flag_wait(&g_cnt[0], target);
        mbar_expect_tx(BAR(B_XI), 5 * XCH);
        bulk_g2s(sb + SM_W, g_X + (size_t)b * 5 * XCH, 5 * XCH, BAR(B_XI));
        TS1(1);
        const uint8_t* wsrc = g_wd + cb * 20480;
        mbar_wait(BAR(B_G1), 0);
        for (int s = 0; s < 4; s++) {
          mbar_expect_tx(BAR(B_F2 + s), 28672);
          bulk_g2s(sb + SM_R2 + s * 28672 + 8192, wsrc + s * 81920, 20480, BAR(B_F2 + s));
        }
        TS1(2);
        flag_wait(&g_cnt[(1 + rb) * 32], target);
        TS1(3);
        const uint8_t* hsrc = g_h + (size_t)rb * 24 * 8192;
        for (int s = 0; s < 4; s++) bulk_g2s(sb + SM_R2 + s * 28672, hsrc + s * 8192, 8192, BAR(B_F2 + s));
        mbar_wait(BAR(B_CD), 0);
        for (int c = 4, s = 4, ph = 1; c < 24; c++) {
          if (c > 4) mbar_wait(BAR(B_E2 + s), ph);
          mbar_expect_tx(BAR(B_F2 + s), 28672);
          bulk_g2s(s == 4 ? sb + SM_W : sb + SM_R2 + s * 28672, hsrc + c * 8192, 8192, BAR(B_F2 + s));
          bulk_g2s(s == 4 ? sb + SM_W + 24576 : sb + SM_R2 + s * 28672 + 8192, wsrc + c * 81920, 20480, BAR(B_F2 + s));
          if (++s == 5) { s = 0; ph ^= 1; }
        }
        TS1(4);
      }
    } else {
      const int hw = warp - 1;
      if (hw == 2) {
        const int c8 = lane & 7, r4 = lane >> 3;
        float acc[4] = {0.f, 0.f, 0.f, 0.f};
        uint4 gw = __ldg((const uint4*)(P.gate_w + c8 * 8));
        uint32_t xs = 0, xph = 0;
#pragma unroll 1
        for (int k = 0; k < 10; k++) {
          const uint4 gn = __ldg((const uint4*)(P.gate_w + (k < 9 ? k + 1 : 0) * 64 + c8 * 8));
          mbar_wait(BAR(B_FX + xs), xph);
#pragma unroll
          for (int i = 0; i < 4; i++) {
            const int row = (i >> 1) * 64 + ct * 8 + (i & 1) * 4 + r4;
            const uint4 v = lds128(sb + SM_X + xs * 16384 + row * 128 + ((c8 ^ (row & 7)) << 4));
            const uint32_t p[4] = {bmul2(v.x, gw.x), bmul2(v.y, gw.y), bmul2(v.z, gw.z), bmul2(v.w, gw.w)};
#pragma unroll
            for (int e = 0; e < 4; e++) acc[i] += __uint_as_float(p[e] << 16) + __uint_as_float(p[e] & 0xffff0000u);
          }
          __syncwarp();
          if (lane == 0 && k < 7) mbar_arrive(BAR(B_EX + xs));
          if (++xs == 3) { xs = 0; xph ^= 1; }
          gw = gn;
        }
#pragma unroll
        for (int i = 0; i < 4; i++)
#pragma unroll
          for (int o = 1; o < 8; o <<= 1) acc[i] += __shfl_xor_sync(0xffffffffu, acc[i], o);
        if (c8 < 4) {
          const float sv = c8 == 0 ? acc[0] : c8 == 1 ? acc[1] : c8 == 2 ? acc[2] : acc[3];
          const float l = __bfloat162float(__float2bfloat16_rn(sv));
          g_gate[rt * 128 + (c8 >> 1) * 64 + ct * 8 + (c8 & 1) * 4 + r4] = __bfloat162float(__float2bfloat16_rn(1.0f / (1.0f + __expf(-l))));
        }
        __syncwarp();
        if (lane == 0) {
          mbar_arrive(BAR(B_G1));
          asm volatile("fence.acq_rel.gpu;" ::: "memory");
          mbar_arrive(BAR(B_HS + 0)); mbar_arrive(BAR(B_HS + 1)); TS1(7);
        }
      } else {
        const int ht = tid - 288;
        const int rc = b >> 1, chb = (b & 1) * 320;
        const __nv_bfloat16* skp = P.shift_k + (chb + lane * 2) * 4;
        uint4 sk = __ldg((const uint4*)(skp + hw * 256));
        if (ht < 20) asm volatile("prefetch.global.L2 [%0];" ::"l"(P.shift_k + chb * 4 + ht * 64));
        for (int i = ht; i < 120; i += 64) *(uint4*)(g_X + (size_t)b * 5 * XCH + (i / 12) * XP + (i % 12) * 16) = make_uint4(0, 0, 0, 0);
        int pg = hw, r = 0;
#pragma unroll 1
        for (int task = hw; task < 20; task += 2) {
          const uint32_t w0 = __byte_perm(sk.x, sk.z, 0x5410), w1 = __byte_perm(sk.x, sk.z, 0x7632);
          const uint32_t w2 = __byte_perm(sk.y, sk.w, 0x5410), w3 = __byte_perm(sk.y, sk.w, 0x7632);
          const int pn = pg >= 3 ? pg - 3 : pg + 2;
          sk = __ldg((const uint4*)(skp + pn * 256));
          mbar_wait(BAR(B_KV + r), 0);
          if (ht == 0) TS1(50 + (task >> 1));
          const uint32_t ka = sb + SM_D + r * 5120 + pg * 128 + lane * 4;
          uint32_t kk[11], o[8];
#pragma unroll
          for (int i = 0; i < 11; i++) kk[i] = lds32(ka + i * 640);
#pragma unroll
          for (int i = 0; i < 8; i++) o[i] = lds32(ka + 22400 + i * 640);
#pragma unroll
          for (int i = 0; i < 8; i++) o[i] = bmul2(bfma2(kk[i + 3], w0, bfma2(kk[i + 2], w1, bfma2(kk[i + 1], w2, bmul2(kk[i], w3)))), o[i]);
          uint8_t* dst = g_X + (size_t)(chb + pg * 64 + lane * 2) * XCH + (r & 1) * XP + (12 + rc * 2 + (r >> 1)) * 16;
          *(uint4*)dst = make_uint4(__byte_perm(o[1], o[0], 0x5410), __byte_perm(o[3], o[2], 0x5410), __byte_perm(o[5], o[4], 0x5410), __byte_perm(o[7], o[6], 0x5410));
          *(uint4*)(dst + XCH) = make_uint4(__byte_perm(o[1], o[0], 0x7632), __byte_perm(o[3], o[2], 0x7632), __byte_perm(o[5], o[4], 0x7632), __byte_perm(o[7], o[6], 0x7632));
          if (pg >= 3) r++;
          pg = pn;
        }
        bar_sync(3, 64);
        if (hw == 1) {
          if (lane < 20) sts128(sb + SM_D + 96 + (lane >> 2) * TP + ((lane >> 1) & 1) * 4128 + (lane & 1) * 16, 0, 0, 0, 0);
          __syncwarp();
          if (lane == 0) {
            asm volatile("fence.proxy.async.shared::cta;" ::: "memory");
            mbar_expect_tx(BAR(B_HR), 20480);
            for (int c = 0; c < 5; c++) bulk_g2s(sb + SM_D + 128 + c * TP + 4128, P.ssm_k + (size_t)(b * 5 + c) * 2048, 4096, BAR(B_HR));
          }
          mbar_wait(BAR(B_HR), 0);
          if (lane == 0) TS1(13);
#pragma unroll 1
          for (int c = 0; c < 5; c++) {
#pragma unroll
            for (int j = 0; j < 2; j++) {
              const uint32_t d = sb + SM_D + 128 + c * TP + j * 2048 + lane * 16;
              uint4 v[4]; uint32_t pv[4];
#pragma unroll
              for (int i = 0; i < 4; i++) { v[i] = lds128(d + 4128 + i * 512); pv[i] = lds32(d + 4124 + i * 512); }
#pragma unroll
              for (int i = 0; i < 4; i++)
                sts128(d + i * 512, __byte_perm(pv[i], v[i].x, 0x5432), __byte_perm(v[i].x, v[i].y, 0x5432), __byte_perm(v[i].y, v[i].z, 0x5432), __byte_perm(v[i].z, v[i].w, 0x5432));
            }
          }
          __syncwarp();
          if (lane == 0) { mbar_arrive(BAR(B_HC)); TS1(14); }
        } else if (lane == 0) {
          TR(ta);
          mbar_wait(BAR(B_WD), 0);
          if (b < 120) bulk_s2g(g_wd + (size_t)b * 16384, sb + SM_GAP, 16384);
          asm volatile("cp.async.bulk.commit_group;" ::: "memory");
          asm volatile("fence.acq_rel.gpu;" ::: "memory");
          TR(tb);
          asm volatile("cp.async.bulk.wait_group 0;" ::: "memory");
          uint32_t old;
          asm volatile("atom.relaxed.gpu.global.add.u32 %0, [%1], 1;" : "=r"(old) : "l"(&g_cnt[0]) : "memory");
          *s_target = (old & ~127u) + 128u;
          mbar_arrive(BAR(B_PRE));
          TS1(8); TW(6, ta); TW(20, tb);
        }
        if (lane == 0) {
          mbar_wait(BAR(B_HS + hw), 0);
          TR(t0);
          bulk_s2g(g_h + ((size_t)(rt * 2 + hw) * 24 + ct * 3) * 8192, sb + SM_W + (1 + hw) * 24576, 24576);
          asm volatile("cp.async.bulk.commit_group;" ::: "memory");
          asm volatile("cp.async.bulk.wait_group 0;" ::: "memory");
          flag_add_relaxed(&g_cnt[(1 + rt * 2 + hw) * 32], 16);
          mbar_arrive(BAR(B_HF + hw));
          TR(t1);
          if (hw == 0) {
            const uint32_t target = *s_target;
            mbar_wait(BAR(B_CD), 0);
            TR(t2);
            for (int c = 0; c < C0; c++) bulk_s2g(g_z + (size_t)(b * 5 + c) * 4096, sb + SM_D + 128 + c * TP, 4096);
            asm volatile("cp.async.bulk.commit_group;" ::: "memory");
            asm volatile("cp.async.bulk.wait_group 0;" ::: "memory");
            flag_add_relaxed(&g_cnt[(33 + cb) * 32], 2);
            TR(t3);
            flag_wait(&g_cnt[(1 + rb) * 32], target);
            mbar_expect_tx(BAR(B_Q), 256);
            bulk_g2s(sb + SM_GT, g_gate + rb * 64, 256, BAR(B_Q));
            TW(32, t2); TW(33, t3);
          }
          TW(30 + hw * 8, t0); TW(31 + hw * 8, t1);
        }
      }
    }
  } else {
    asm volatile("setmaxnreg.inc.sync.aligned.u32 232;");
    const int t128 = tid & 127, w = __shfl_sync(0xffffffffu, t128 >> 5, 0), lane = tid & 31;
    {
      float ag[96], au[96];
      const uint64_t dA0 = mkdesc(sb + SM_X + wg * 8192, 16, 1024, 1);
      const uint64_t dB0 = mkdesc(sb + SM_W, 4096, 1024, 1);
      const uint32_t xa = sb + SM_X + wg * 8192 + (16 * w + (lane & 15)) * 128 + (((lane >> 4) ^ (lane & 7)) << 4);
      uint4 A[2];
      mbar_wait(BAR(B_FX + 0), 0);
      A[0] = ldsm4(xa);
#pragma unroll
      for (int st = 0; st < 28; st++) {
        const int k = st >> 2, kk = st & 3, n = st >> 1, xs = k % 3;
        if (!(st & 1)) mbar_wait(BAR(B_FW + n % 5), (n / 5) & 1);
        if (kk == 0) TS(20 + k);
        WG_FENCE();
        wgmma_rs_tb_n192(ag, A[st & 1], dB0 + (n % 5) * 1536 + (st & 1) * 128, st > 0);
        wgmma_rs_tb_n192(au, A[st & 1], dB0 + (n % 5) * 1536 + 768 + (st & 1) * 128, st > 0);
        WG_COMMIT();
        if (kk == 3 && lane == 0) mbar_arrive(BAR(B_EX + xs));
        WG_WAIT(1);
        if (!(st & 1) && st > 0 && lane == 0) mbar_arrive(BAR(B_EW + (n - 1) % 5));
        if (kk < 3) A[(kk + 1) & 1] = ldsm4((xa ^ ((kk + 1) << 5)) + xs * 16384);
        else if (k < 6) { mbar_wait(BAR(B_FX + (k + 1) % 3), ((k + 1) / 3) & 1); A[0] = ldsm4(xa + ((k + 1) % 3) * 16384); }
      }
      TS(1);
#define G1_UNIT(acc, xsl, wsl) { WG_FENCE(); _Pragma("unroll") for (int kk = 0; kk < 4; kk++) wgmma_ss_tb_n192(acc, dA0 + (xsl) * 1024 + kk * 2, dB0 + (wsl) * 1536 + (kk >> 1) * 768 + (kk & 1) * 128, 1); WG_COMMIT(); }
      mbar_wait(BAR(B_FX + 1), 0);
      mbar_wait(BAR(B_FW + 4), 0);
      G1_UNIT(ag, 1, 4);
      WG_WAIT(1);
      if (lane == 0) mbar_arrive(BAR(B_EW + 3));
      mbar_wait(BAR(B_FX + 2), 0);
      mbar_wait(BAR(B_FW + 0), 1);
      G1_UNIT(ag, 2, 0);
      WG_WAIT(1);
      if (lane == 0) mbar_arrive(BAR(B_EW + 4));
      mbar_wait(BAR(B_FX + 0), 1);
      mbar_wait(BAR(B_FW + 1), 1);
      G1_UNIT(ag, 0, 1);
      WG_WAIT(1);
      if (lane == 0) mbar_arrive(BAR(B_EW + 0));
      bar_sync(4, 256);
      mbar_wait(BAR(B_FW + 2), 1);
      G1_UNIT(au, 1, 2);
      TS(14);
      WG_WAIT(1);
      if (lane == 0) mbar_arrive(BAR(B_EW + 1));
      TS(2);
      uint32_t sg[48];
#define SIG(lo, hi) _Pragma("unroll") for (int i = lo; i < hi; i++) sg[i] = pack_bf16(sigmoidf_fast(ag[2 * i]), sigmoidf_fast(ag[2 * i + 1]));
      SIG(0, SG0)
      TS(15);
      mbar_wait(BAR(B_FW + 3), 1);
      WG_FENCE();
#define U1(xsl, wsl, kk) wgmma_ss_tb_n192(au, dA0 + (xsl) * 1024 + kk * 2, dB0 + (wsl) * 1536 + (kk >> 1) * 768 + (kk & 1) * 128, 1);
      U1(2, 3, 0) SIG(SG0, SG0 + SG1)
      U1(2, 3, 1) SIG(SG0 + SG1, SG0 + 2 * SG1)
      U1(2, 3, 2) SIG(SG0 + 2 * SG1, SG0 + 3 * SG1)
      U1(2, 3, 3) WG_COMMIT(); SIG(SG0 + 3 * SG1, SG0 + 4 * SG1)
      TS(17);
      mbar_wait(BAR(B_FW + 4), 1);
      WG_FENCE();
      U1(0, 4, 0) SIG(SG0 + 4 * SG1, SG0 + 5 * SG1)
      U1(0, 4, 1) SIG(SG0 + 5 * SG1, SG0 + 6 * SG1)
      U1(0, 4, 2) SIG(SG0 + 6 * SG1, SG0 + 7 * SG1)
      U1(0, 4, 3) WG_COMMIT(); WG_WAIT(2);
      if (lane == 0) mbar_arrive(BAR(B_EW + 2));
      SIG(SG0 + 7 * SG1, 48)
      TS(3);
      mbar_wait(BAR(B_EW + 1 + wg), 1);
      WG_WAIT(0);
      if (lane == 0) mbar_arrive(BAR(B_G1));
      TS(4);
      const uint32_t hb = sb + SM_W + (1 + wg) * 24576 + (16 * w + (lane & 15)) * 128;
#pragma unroll
      for (int j = 0; j < 24; j += 2) {
        uint32_t p[4];
#pragma unroll
        for (int e = 0; e < 4; e++) p[e] = bmul2(sg[2 * j + e], pack_bf16(au[4 * j + 2 * e], au[4 * j + 2 * e + 1]));
        const int cc = (j & 7) + (lane >> 4);
        stsm4(hb + (j >> 3) * 8192 + ((cc ^ (lane & 7)) << 4), p[0], p[1], p[2], p[3]);
      }
      asm volatile("fence.proxy.async.shared::cta;" ::: "memory");
      mbar_arrive(BAR(B_HS + wg));
      TS(5);
    }
    {
      const int g = lane >> 2, t = lane & 3;
      const uint32_t ra0 = sb + SM_D + 128 + ((g & 1) ? 4128 + 2 * (128 * w + g - 2 * t - 9) : 2 * (128 * w + g - 2 * t - 8));
      const uint32_t pbase = sb + SM_W + (1 + wg) * 24576;
      const uint32_t pa = pbase + w * (2 * PP) + ((lane >> 3) & 1) * PP + (8 * (lane >> 4) + (lane & 7) + 8 * w) * 16;
      mbar_wait(BAR(B_HC), 0);
      mbar_wait(BAR(B_XI), 0);
      const int c_beg = wg ? C0 : 0, c_end = wg ? 5 : C0;
      auto reduce = [&](int c) {
        const uint32_t dv = __ldg((const unsigned short*)(P.ssm_D + b * 5 + c));
        bar_sync(1 + wg, 128);
        const uint32_t D2 = dv | (dv << 16);
#pragma unroll
        for (int cc = 0; cc < 2; cc++) {
          const int a = cc * 64 + (t128 >> 1), half = t128 & 1;
          float y[8];
#pragma unroll
          for (int q = 0; q < 4; q++) {
            uint4 v = make_uint4(0, 0, 0, 0);
            if (cc == 1 || a >= 8 * q) v = lds128(pbase + q * (2 * PP) + half * PP + a * 16);
            const uint32_t u[4] = {v.x, v.y, v.z, v.w};
#pragma unroll
            for (int e = 0; e < 4; e++) {
              const float lo = __uint_as_float(u[e] << 16), hi = __uint_as_float(u[e] & 0xffff0000u);
              if (q == 0) { y[2 * e] = lo; y[2 * e + 1] = hi; } else { y[2 * e] += lo; y[2 * e + 1] += hi; }
            }
          }
          const uint4 xv = lds128(sb + SM_W + c * XCH + half * XP + (a + 12) * 16);
          const uint32_t xu[4] = {xv.x, xv.y, xv.z, xv.w};
          uint32_t o[4];
#pragma unroll
          for (int e = 0; e < 4; e++) o[e] = badd2(pack_bf16(y[2 * e], y[2 * e + 1]), bmul2(__byte_perm(xu[e], 0, 0x1032), D2));
          sts128(sb + SM_D + 128 + c * TP + cc * 2048 + t128 * 16, o[0], o[1], o[2], o[3]);
        }
        asm volatile("fence.proxy.async.shared::cta;" ::: "memory");
      };
      uint32_t A0[16], A1[16], A2[16];
      conv_ldA<0>(A0, ra0 + c_beg * TP, zz); conv_ldA<128>(A1, ra0 + c_beg * TP, zz);
      if (TOK && wg) bar_sync(5, 256);
#pragma unroll 1
      for (int c = c_beg; c < c_end; c++) {
        const uint32_t ra = ra0 + c * TP;
        const uint64_t dX = mkdesc(sb + SM_W + c * XCH + 192, XP, 128, 0);
        float T0[64], T1[16], T2[32], T3[16];
#define TSC(i) if (c == c_beg + TSCH) TS(i);
#define TOKEN(i) if (TOK == i && c == 0) bar_arrive(5, 256);
        TSC(27)
        conv_grp<128, 0>(T0, A0, dX);
        conv_grp<128, 1>(T0, A1, dX); TOKEN(1)
        conv_ldA<3072>(A2, ra, zz);
        TSC(28)
        if (c > c_beg) reduce(c - 1);
        TSC(29)
        conv_grp<32, 0>(T3, A2, dX); TOKEN(2)
        WG_WAIT(2); conv_ldA<3072 + 128>(A0, ra, zz);
        conv_grp<32, 1>(T3, A0, dX); TOKEN(3)
        WG_WAIT(2); TSC(30) conv_ldA<1024>(A1, ra, zz);
        conv_grp2<0>(T2, T1, A1, dX); TOKEN(4)
        WG_WAIT(2); TSC(31) conv_ldA<1024 + 128>(A2, ra, zz);
        conv_grp2<1>(T2, T1, A2, dX); TOKEN(5)
        WG_WAIT(2); TSC(59) conv_ldA<2048>(A0, ra, zz);
        conv_grp<64, 0, 1>(T2, A0, dX); TOKEN(6)
#pragma unroll
        for (int i = 0; i < 16; i++) fadd_v(T0[48 + i], T3[i]);
        WG_WAIT(2); TSC(60) conv_ldA<2048 + 128>(A1, ra, zz);
        conv_grp<64, 1>(T2, A1, dX); TOKEN(7)
        WG_WAIT(2); TSC(61)
#pragma unroll
        for (int i = 0; i < 16; i++) fadd_v(T0[16 + i], T1[i]);
        const uint32_t rn = c < 4 ? ra + TP : ra;
        WG_WAIT(1); conv_ldA<0>(A0, rn, zz);
        if (c == c_beg) mbar_wait(BAR(B_HF + wg), 0);
        WG_WAIT(0); conv_ldA<128>(A1, rn, zz);
        TS(56 + c - c_beg);
#pragma unroll
        for (int i = 0; i < 32; i++) T0[32 + i] += T2[i];
        bar_sync(1 + wg, 128);
        if (wg && c > c_beg && t128 == 0) bulk_s2g(g_z + (size_t)(b * 5 + c - 1) * 4096, sb + SM_D + 128 + (c - 1) * TP, 4096);
#pragma unroll
        for (int j = 0; j < 16; j += 2)
          stsm4t(pa + j * 128, pack_bf16(T0[4 * j], T0[4 * j + 1]), pack_bf16(T0[4 * j + 2], T0[4 * j + 3]), pack_bf16(T0[4 * j + 4], T0[4 * j + 5]), pack_bf16(T0[4 * j + 6], T0[4 * j + 7]));
        TS(6 + c - c_beg);
      }
      reduce(c_end - 1);
      if (wg == 0) mbar_arrive(BAR(B_CD));
    }
    if (wg == 0) {
      const int g = lane >> 2;
      const int frow = 16 * w + (lane & 7) + 8 * ((lane >> 3) & 1);
      const uint32_t fo = frow * 64 + (((lane >> 4) ^ ((frow >> 1) & 3)) << 4);
      const uint32_t za = sb + SM_D + ((lane & 7) + 8 * (lane >> 4)) * 128 + (((2 * w + ((lane >> 3) & 1)) ^ (lane & 7)) << 4);
      float acc[80];
#pragma unroll
      for (int i = 0; i < 80; i++) acc[i] = 0.f;
      uint4 ga[10];
      uint32_t g0 = 0, g1 = 0;
#define GA_STEP(p) { \
        if (p == 0) { const float gv0 = __uint_as_float(lds32(sb + SM_GT + (16 * w + g) * 4)), gv1 = __uint_as_float(lds32(sb + SM_GT + (16 * w + g + 8) * 4)); g0 = pack_bf16(gv0, gv0); g1 = pack_bf16(gv1, gv1); } \
        _Pragma("unroll") for (int j = 2 * p; j < 2 * p + 2; j++) { \
          const uint4 z = ldsm4t(za + j * 2048); \
          const uint4 q = ldsm4(sb + SM_D + 20480 + p * 4096 + (fo ^ ((j & 1) << 5))); \
          ga[j] = make_uint4(bmul2(g0, bmul2(q.x, z.x)), bmul2(g1, bmul2(q.y, z.y)), bmul2(g0, bmul2(q.z, z.z)), bmul2(g1, bmul2(q.w, z.w))); \
        } }
      const uint64_t dA0 = mkdesc(sb + SM_R2, 16, 1024, 1), dA4 = mkdesc(sb + SM_W, 16, 1024, 1);
      const uint64_t dB0 = mkdesc(sb + SM_R2 + 8192, 4096, 512, 2), dB4 = mkdesc(sb + SM_W + 24576, 4096, 512, 2);
      mbar_wait(BAR(B_F2), 0);
      bool pend = false;
      int step = 0, s = 0, ph = 0, sp = 0;
#pragma unroll 1
      for (int c = 0; c < 24; c++) {
        const uint64_t dA = s == 4 ? dA4 : dA0 + s * 1792, dB = s == 4 ? dB4 : dB0 + s * 1792;
        TS(32 + c);
        WG_FENCE();
#pragma unroll
        for (int kk = 0; kk < 4; kk++) wgmma_ss_tb_n160(acc, dA + kk * 2, dB + kk * 64, 1);
        WG_COMMIT();
        if (pend) { WG_WAIT(1); if (lane == 0) mbar_arrive(BAR(B_E2 + sp)); }
        if (c == 23) break;
        if (step < 5 && (step > 0 || __all_sync(0xffffffffu, mbar_test(BAR(B_Q), 0)))) {
          if (step == 0) GA_STEP(0) else if (step == 1) GA_STEP(1) else if (step == 2) GA_STEP(2) else if (step == 3) GA_STEP(3) else GA_STEP(4)
          step++;
        }
        sp = s;
        if (++s == 5) { s = 0; ph ^= 1; }
        pend = __all_sync(0xffffffffu, mbar_test(BAR(B_F2 + s), ph));
        if (!pend) {
          WG_WAIT(0);
          if (lane == 0) mbar_arrive(BAR(B_E2 + sp));
          mbar_wait(BAR(B_F2 + s), ph);
        }
      }
      TS(11);
      if (step == 0) { mbar_wait(BAR(B_Q), 0); GA_STEP(0) }
      if (step <= 1) GA_STEP(1)
      if (step <= 2) GA_STEP(2)
      if (step <= 3) GA_STEP(3)
      if (step <= 4) GA_STEP(4)
      const float gv0 = __uint_as_float(g0 << 16), gv1 = __uint_as_float(g1 << 16);
      const uint32_t om0 = pack_bf16(1.0f - gv0, 1.0f - gv0), om1 = pack_bf16(1.0f - gv1, 1.0f - gv1);
      WG_WAIT(0);
      TS(12);
#pragma unroll
      for (int j = 0; j < 10; j++) {
        const uint32_t o0 = badd2(ga[j].x, bmul2(om0, pack_bf16(acc[8 * j + 0], acc[8 * j + 1])));
        const uint32_t o1 = badd2(ga[j].y, bmul2(om1, pack_bf16(acc[8 * j + 2], acc[8 * j + 3])));
        const uint32_t o2 = badd2(ga[j].z, bmul2(om0, pack_bf16(acc[8 * j + 4], acc[8 * j + 5])));
        const uint32_t o3 = badd2(ga[j].w, bmul2(om1, pack_bf16(acc[8 * j + 6], acc[8 * j + 7])));
        stsm4(sb + SM_W + 2 * 24576 + (j >> 1) * 4096 + (fo ^ ((j & 1) << 5)), o0, o1, o2, o3);
      }
      asm volatile("fence.proxy.async.shared::cta;" ::: "memory");
      bar_sync(1, 128);
      if (t128 == 0) {
        tma3d_store(&maps.o, sb + SM_W + 2 * 24576, 0, rb * 64, cb * 5);
        asm volatile("cp.async.bulk.commit_group;" ::: "memory");
        asm volatile("cp.async.bulk.wait_group.read 0;" ::: "memory");
      }
      TS(13);
    } else {
      bar_sync(2, 128);
      if (t128 == 0) {
        bulk_s2g(g_z + (size_t)(b * 5 + 4) * 4096, sb + SM_D + 128 + 4 * TP, 4096);
        asm volatile("cp.async.bulk.commit_group;" ::: "memory");
        asm volatile("cp.async.bulk.wait_group 0;" ::: "memory");
        flag_add_relaxed(&g_cnt[(33 + cb) * 32], 2);
        TS(9);
        flag_wait(&g_cnt[(33 + cb) * 32], *s_target);
        TS(12);
        mbar_expect_tx(BAR(B_Q), 40960);
        tma2d(sb + SM_D, &maps.z, BAR(B_Q), rb * 64, cb * 160);
        tma3d(sb + SM_D + 20480, &maps.q, BAR(B_Q), 0, rb * 64, cb * 5);
      }
    }
  }
}

typedef CUresult (*EncFn)(CUtensorMap*, CUtensorMapDataType, cuuint32_t, void*, const cuuint64_t*, const cuuint64_t*, const cuuint32_t*, const cuuint32_t*,
                          CUtensorMapInterleave, CUtensorMapSwizzle, CUtensorMapL2promotion, CUtensorMapFloatOOBfill);

void enc(EncFn fn, CUtensorMap* m, CUtensorMapDataType dt, int rank, const void* p, const cuuint64_t* gd, const cuuint64_t* gs, const cuuint32_t* bd, CUtensorMapSwizzle sw) {
  cuuint32_t es[5] = {1, 1, 1, 1, 1};
  fn(m, dt, rank, (void*)p, gd, gs, bd, es, CU_TENSOR_MAP_INTERLEAVE_NONE, sw, CU_TENSOR_MAP_L2_PROMOTION_L2_128B, CU_TENSOR_MAP_FLOAT_OOB_FILL_NONE);
}

}

extern "C" void kernel_launch(void* const* d_in, const int* in_sizes, int n_in, void* d_out, int out_size) {
  static EncFn fn = nullptr;
  static void* zp = nullptr;
  if (!fn) {
    cudaGetSymbolAddress(&zp, g_z);
    void* f = nullptr; cudaDriverEntryPointQueryResult qr;
    cudaGetDriverEntryPoint("cuTensorMapEncodeTiled", &f, cudaEnableDefault, &qr);
    fn = (EncFn)f;
    cudaFuncSetAttribute(fused_kernel, cudaFuncAttributeMaxDynamicSharedMemorySize, SM_TOTAL);
  }
  Maps m;
  const CUtensorMapDataType BF = CU_TENSOR_MAP_DATA_TYPE_BFLOAT16;
  { cuuint64_t gd[2] = {640, 2048}, gs[1] = {1280}; cuuint32_t bd[2] = {64, 128}; enc(fn, &m.x, BF, 2, d_in[0], gd, gs, bd, CU_TENSOR_MAP_SWIZZLE_128B); }
  { cuuint64_t gd[3] = {64, 640, 24}, gs[2] = {3072, 128}; cuuint32_t bd[3] = {64, 32, 3};
    enc(fn, &m.wg, BF, 3, d_in[7], gd, gs, bd, CU_TENSOR_MAP_SWIZZLE_128B); enc(fn, &m.wu, BF, 3, d_in[8], gd, gs, bd, CU_TENSOR_MAP_SWIZZLE_128B); }
  { cuuint64_t gd[3] = {32, 1536, 20}, gs[2] = {1280, 64}; cuuint32_t bd[3] = {32, 64, 4}; enc(fn, &m.wd, BF, 3, d_in[9], gd, gs, bd, CU_TENSOR_MAP_SWIZZLE_64B); }
  { cuuint64_t gd[2] = {320, 2048}, gs[1] = {1280}; cuuint32_t b3[2] = {160, 3}, b8[2] = {160, 8};
    enc(fn, &m.k3, CU_TENSOR_MAP_DATA_TYPE_UINT32, 2, d_in[1], gd, gs, b3, CU_TENSOR_MAP_SWIZZLE_NONE);
    enc(fn, &m.k8, CU_TENSOR_MAP_DATA_TYPE_UINT32, 2, d_in[1], gd, gs, b8, CU_TENSOR_MAP_SWIZZLE_NONE);
    enc(fn, &m.v8, CU_TENSOR_MAP_DATA_TYPE_UINT32, 2, d_in[2], gd, gs, b8, CU_TENSOR_MAP_SWIZZLE_NONE); }
  { cuuint64_t gd[3] = {32, 2048, 20}, gs[2] = {1280, 64}; cuuint32_t bd[3] = {32, 64, 5};
    enc(fn, &m.q, BF, 3, d_in[0], gd, gs, bd, CU_TENSOR_MAP_SWIZZLE_64B); enc(fn, &m.o, BF, 3, d_out, gd, gs, bd, CU_TENSOR_MAP_SWIZZLE_64B); }
  { cuuint64_t gd[2] = {2048, 640}, gs[1] = {4096}; cuuint32_t bd[2] = {64, 160}; enc(fn, &m.z, BF, 2, zp, gd, gs, bd, CU_TENSOR_MAP_SWIZZLE_128B); }
  Ptrs p;
  p.x = (const __nv_bfloat16*)d_in[0]; p.shift_k = (const __nv_bfloat16*)d_in[3]; p.ssm_k = (const __nv_bfloat16*)d_in[4];
  p.ssm_D = (const __nv_bfloat16*)d_in[5]; p.gate_w = (const __nv_bfloat16*)d_in[10];
  fused_kernel<<<128, 384, SM_TOTAL, cudaStreamPerThread>>>(m, p, 0u);
}
```

```cpp
#include <cuda_runtime.h>
#include <cuda_bf16.h>
#include <cuda.h>
#include <stdint.h>

namespace {

constexpr int XP = 2304;
constexpr int XCH = 2 * XP;
constexpr int TP = 8320;
#define KV0 3
#define KV1 4
#define KV2 5
#define KV3 6
#define KV4 7
#define NPRE 1
#define PD 10
#define PF0 10
#define LSTEP 0
#define WD_N 8
#define SK_N 9
#define MAP1 1
#define MAP2 1
#define SGB 8
#define HOFF 2
#define PF_N 14
#define X9_N 15
#define WK 5
#define SG0 40
#define SG1 4

constexpr uint32_t SM_W = 0;
constexpr uint32_t SM_X = 122880;
constexpr uint32_t SM_R2 = 73728;
constexpr uint32_t SM_D = 188416;
constexpr uint32_t SM_BAR = 231296;
constexpr uint32_t SM_GAP = 172032;
constexpr uint32_t SM_GT = SM_BAR + 592;
constexpr uint32_t SM_GO = SM_GT + 256;
constexpr uint32_t SM_TOTAL = SM_GO + 64;
enum { B_FX = 0  , B_FW = 3  , B_KV = 8  , B_F2 = 13  , B_WD = 18, B_XI = 19, B_HR = 20, B_HF = 21  , B_Q2 = 23, B_F9 = 24, B_GF = 25, B_PRE = 26,
       B_EW = 30  , B_EX = 36  , B_G1 = 39, B_E2 = 42  , B_HC = 48, B_Q = 49, B_KD = 50, B_HS = 54  , B_ZR = 60  , B_GA = 65, B_PF = 66   };

__device__ __align__(1024) uint8_t g_X[640 * 4096];
__device__ __align__(1024) uint8_t g_h[2048 * 1536 * 2];
__device__ __align__(1024) uint8_t g_wd[1536 * 640 * 2];
__device__ __align__(1024) uint8_t g_z[640 * 4096];
__device__ __align__(1024) float g_gate[2048];
__device__ uint32_t g_cnt[44 * 32];
#define TS(i)
#define TS1(i)
#define TR(v)
#define TW(i, v)

struct Maps { CUtensorMap x, wg, wu, wd, k, v, q, o, z, xs, xl; };
struct Ptrs { const __nv_bfloat16 *x, *shift_k, *ssm_k, *ssm_D, *gate_w, *wg, *wu; };

__device__ __forceinline__ uint32_t smem_u32(const void* p) { return (uint32_t)__cvta_generic_to_shared(p); }
__device__ __forceinline__ bool elect_one() { uint32_t p; asm volatile("{.reg .pred P; elect.sync _|P, 0xffffffff; selp.u32 %0, 1, 0, P;}" : "=r"(p)); return p; }
__device__ __forceinline__ void mbar_init(uint32_t bar, uint32_t cnt) { asm volatile("mbarrier.init.shared::cta.b64 [%0], %1;" ::"r"(bar), "r"(cnt)); }
__device__ __forceinline__ void mbar_expect_tx(uint32_t bar, uint32_t bytes) { asm volatile("mbarrier.arrive.expect_tx.shared::cta.b64 _, [%0], %1;" ::"r"(bar), "r"(bytes) : "memory"); }
__device__ __forceinline__ void mbar_arrive(uint32_t bar) { asm volatile("mbarrier.arrive.shared::cta.b64 _, [%0];" ::"r"(bar) : "memory"); }
__device__ __forceinline__ void mbar_wait(uint32_t bar, uint32_t parity) {
  uint32_t ok;
  asm volatile("{.reg .pred p; mbarrier.try_wait.parity.shared::cta.b64 p, [%1], %2; selp.u32 %0,1,0,p;}" : "=r"(ok) : "r"(bar), "r"(parity) : "memory");
  if (!ok) {
    uint32_t it = 0;
    do {
      asm volatile("{.reg .pred p; mbarrier.try_wait.parity.shared::cta.b64 p, [%1], %2, 2000; selp.u32 %0,1,0,p;}" : "=r"(ok) : "r"(bar), "r"(parity) : "memory");
    } while (!ok && ++it < 100000u);
  }
}
__device__ __forceinline__ void flag_wait(const uint32_t* p, uint32_t target) {
  uint32_t v, it = 0;
  while (true) {
    asm volatile("ld.acquire.gpu.global.u32 %0, [%1];" : "=r"(v) : "l"(p) : "memory");
    if ((int)(v - target) >= 0) break;
    if (++it > 400000u) break;
    __nanosleep(20);
  }
  asm volatile("fence.proxy.async.global;" ::: "memory");
}
__device__ __forceinline__ void flag_add(uint32_t* p, uint32_t v) {
  asm volatile("red.release.gpu.global.add.u32 [%0], %1;" ::"l"(p), "r"(v) : "memory");
}
__device__ __forceinline__ void flag_add_relaxed(uint32_t* p, uint32_t v) {
  asm volatile("red.relaxed.gpu.global.add.u32 [%0], %1;" ::"l"(p), "r"(v) : "memory");
}
__device__ __forceinline__ bool mbar_test(uint32_t bar, uint32_t parity) {
  uint32_t ok;
  asm volatile("{.reg .pred p; mbarrier.test_wait.parity.shared::cta.b64 p, [%1], %2; selp.u32 %0,1,0,p;}" : "=r"(ok) : "r"(bar), "r"(parity) : "memory");
  return ok;
}
__device__ __forceinline__ void cp_async16(uint32_t dst, const void* src) { asm volatile("cp.async.cg.shared.global [%0], [%1], 16;" ::"r"(dst), "l"(src) : "memory"); }
__device__ __forceinline__ void tma2d(uint32_t dst, const CUtensorMap* m, uint32_t bar, int c0, int c1) {
  asm volatile("cp.async.bulk.tensor.2d.shared::cluster.global.mbarrier::complete_tx::bytes [%0], [%1, {%3,%4}], [%2];" ::"r"(dst), "l"(m), "r"(bar), "r"(c0), "r"(c1) : "memory");
}
__device__ __forceinline__ void tma3d(uint32_t dst, const CUtensorMap* m, uint32_t bar, int c0, int c1, int c2) {
  asm volatile("cp.async.bulk.tensor.3d.shared::cluster.global.mbarrier::complete_tx::bytes [%0], [%1, {%3,%4,%5}], [%2];" ::"r"(dst), "l"(m), "r"(bar), "r"(c0), "r"(c1), "r"(c2) : "memory");
}
__device__ __forceinline__ void tma3d_store(const CUtensorMap* m, uint32_t src, int c0, int c1, int c2) {
  asm volatile("cp.async.bulk.tensor.3d.global.shared::cta.bulk_group [%0, {%2,%3,%4}], [%1];" ::"l"(m), "r"(src), "r"(c0), "r"(c1), "r"(c2) : "memory");
}
__device__ __forceinline__ void bulk_g2s(uint32_t dst, const void* src, uint32_t bytes, uint32_t bar) {
  asm volatile("cp.async.bulk.shared::cluster.global.mbarrier::complete_tx::bytes [%0], [%1], %2, [%3];" ::"r"(dst), "l"(src), "r"(bytes), "r"(bar) : "memory");
}
__device__ __forceinline__ void bulk_s2g(void* dst, uint32_t src, uint32_t bytes) {
  asm volatile("cp.async.bulk.global.shared::cta.bulk_group [%0], [%1], %2;" ::"l"(dst), "r"(src), "r"(bytes) : "memory");
}
__device__ __forceinline__ void l2_prefetch(const void* src, uint32_t bytes) {
  asm volatile("cp.async.bulk.prefetch.L2.global [%0], %1;" ::"l"(src), "r"(bytes) : "memory");
}
__device__ __forceinline__ void tma3d_prefetch(const CUtensorMap* m, int c0, int c1, int c2) {
  asm volatile("cp.async.bulk.prefetch.tensor.3d.L2.global.tile [%0, {%1,%2,%3}];" ::"l"(m), "r"(c0), "r"(c1), "r"(c2) : "memory");
}
__device__ __forceinline__ void tmap_prefetch(const CUtensorMap* m) { asm volatile("prefetch.tensormap [%0];" ::"l"(m) : "memory"); }
__device__ __forceinline__ uint64_t mkdesc(uint32_t addr, uint32_t lbo, uint32_t sbo, uint32_t swz) {
  return (uint64_t)((addr & 0x3FFFF) >> 4) | ((uint64_t)(lbo >> 4) << 16) | ((uint64_t)(sbo >> 4) << 32) | ((uint64_t)swz << 62);
}
#define WG_FENCE() asm volatile("wgmma.fence.sync.aligned;" ::: "memory")
#define WG_COMMIT() asm volatile("wgmma.commit_group.sync.aligned;" ::: "memory")
#define WG_WAIT(n) asm volatile("wgmma.wait_group.sync.aligned " #n ";" ::: "memory")
__device__ __forceinline__ void bar_sync(int id, int n) { asm volatile("bar.sync %0, %1;" ::"r"(id), "r"(n) : "memory"); }
__device__ __forceinline__ void bar_arrive(int id, int n) { asm volatile("bar.arrive %0, %1;" ::"r"(id), "r"(n) : "memory"); }
__device__ __forceinline__ uint32_t pack_bf16(float lo, float hi) { uint32_t r; asm("cvt.rn.bf16x2.f32 %0, %1, %2;" : "=r"(r) : "f"(hi), "f"(lo)); return r; }
__device__ __forceinline__ uint32_t bmul2(uint32_t a, uint32_t b) { uint32_t r; asm("mul.rn.bf16x2 %0, %1, %2;" : "=r"(r) : "r"(a), "r"(b)); return r; }
__device__ __forceinline__ uint32_t badd2(uint32_t a, uint32_t b) { uint32_t r; asm("add.rn.bf16x2 %0, %1, %2;" : "=r"(r) : "r"(a), "r"(b)); return r; }
__device__ __forceinline__ uint32_t bfma2(uint32_t a, uint32_t b, uint32_t c) { uint32_t r; asm("fma.rn.bf16x2 %0, %1, %2, %3;" : "=r"(r) : "r"(a), "r"(b), "r"(c)); return r; }
__device__ __forceinline__ uint32_t lds32(uint32_t a) { uint32_t r; asm volatile("ld.shared.u32 %0, [%1];" : "=r"(r) : "r"(a)); return r; }
__device__ __forceinline__ uint32_t lds32v(uint32_t a) { uint32_t r; asm volatile("ld.shared.u32 %0, [%1];" : "=r"(r) : "r"(a) : "memory"); return r; }
__device__ __forceinline__ uint4 lds128(uint32_t a) { uint4 v; asm volatile("ld.shared.v4.u32 {%0,%1,%2,%3}, [%4];" : "=r"(v.x), "=r"(v.y), "=r"(v.z), "=r"(v.w) : "r"(a)); return v; }
__device__ __forceinline__ void sts128(uint32_t a, uint32_t x, uint32_t y, uint32_t z, uint32_t w) { asm volatile("st.shared.v4.u32 [%0], {%1,%2,%3,%4};" ::"r"(a), "r"(x), "r"(y), "r"(z), "r"(w) : "memory"); }
__device__ __forceinline__ void stsm4(uint32_t a, uint32_t x, uint32_t y, uint32_t z, uint32_t w) { asm volatile("stmatrix.sync.aligned.m8n8.x4.shared.b16 [%0], {%1,%2,%3,%4};" ::"r"(a), "r"(x), "r"(y), "r"(z), "r"(w) : "memory"); }
__device__ __forceinline__ void stsm4t(uint32_t a, uint32_t x, uint32_t y, uint32_t z, uint32_t w) { asm volatile("stmatrix.sync.aligned.m8n8.x4.trans.shared.b16 [%0], {%1,%2,%3,%4};" ::"r"(a), "r"(x), "r"(y), "r"(z), "r"(w) : "memory"); }
__device__ __forceinline__ uint4 ldsm4(uint32_t a) { uint4 v; asm volatile("ldmatrix.sync.aligned.m8n8.x4.shared.b16 {%0,%1,%2,%3}, [%4];" : "=r"(v.x), "=r"(v.y), "=r"(v.z), "=r"(v.w) : "r"(a) : "memory"); return v; }
__device__ __forceinline__ uint4 ldsm4t(uint32_t a) { uint4 v; asm volatile("ldmatrix.sync.aligned.m8n8.x4.trans.shared.b16 {%0,%1,%2,%3}, [%4];" : "=r"(v.x), "=r"(v.y), "=r"(v.z), "=r"(v.w) : "r"(a) : "memory"); return v; }
__device__ __forceinline__ void tanh_h(float& a) { asm volatile("{.reg .f32 t; mul.f32 t, %0, 0f3F000000; tanh.approx.f32 %0, t;}" : "+f"(a)); }
__device__ __forceinline__ uint32_t sig_fin(float lo, float hi, float h) {
  uint32_t r;
  asm volatile("{.reg .f32 a, b; fma.rn.f32 a, %1, %3, %3; fma.rn.f32 b, %2, %3, %3; cvt.rn.bf16x2.f32 %0, b, a;}" : "=r"(r) : "f"(lo), "f"(hi), "f"(h));
  return r;
}
template <int LO, int HI> __device__ __forceinline__ uint32_t sig_range(float* a, uint32_t* sg, uint32_t zz) {
  uint32_t dep = 0;
#pragma unroll
  for (int b = LO; b < HI; b += SGB) {
    const int e = b + SGB < HI ? b + SGB : HI;
#pragma unroll
    for (int i = 2 * b; i < 2 * e; i++) tanh_h(a[i]);
    const float h = __uint_as_float(0x3f000000u | (__float_as_uint(a[2 * e - 1]) & zz));
#pragma unroll
    for (int i = b; i < e; i++) { sg[i] = sig_fin(a[2 * i], a[2 * i + 1], h); dep |= sg[i]; }
  }
  return dep & zz;
}
__device__ __forceinline__ void fadd_v(float& a, float b) { asm volatile("add.f32 %0, %0, %1;" : "+f"(a) : "f"(b)); }

__device__ __forceinline__ void wgmma_ss_tb_n192(float* d, uint64_t da, uint64_t db, int sc) {
  asm volatile("{.reg .pred p; setp.ne.b32 p, %98, 0;\n"
   "wgmma.mma_async.sync.aligned.m64n192k16.f32.bf16.bf16 {%0,%1,%2,%3,%4,%5,%6,%7,%8,%9,%10,%11,%12,%13,%14,%15,%16,%17,%18,%19,%20,%21,%22,%23,%24,%25,%26,%27,%28,%29,%30,%31,%32,%33,%34,%35,%36,%37,%38,%39,%40,%41,%42,%43,%44,%45,%46,%47,%48,%49,%50,%51,%52,%53,%54,%55,%56,%57,%58,%59,%60,%61,%62,%63,%64,%65,%66,%67,%68,%69,%70,%71,%72,%73,%74,%75,%76,%77,%78,%79,%80,%81,%82,%83,%84,%85,%86,%87,%88,%89,%90,%91,%92,%93,%94,%95}, %96, %97, p, 1, 1, 0, 1;}\n"
   : "+f"(d[0]),"+f"(d[1]),"+f"(d[2]),"+f"(d[3]),"+f"(d[4]),"+f"(d[5]),"+f"(d[6]),"+f"(d[7]),"+f"(d[8]),"+f"(d[9]),"+f"(d[10]),"+f"(d[11]),"+f"(d[12]),"+f"(d[13]),"+f"(d[14]),"+f"(d[15]),"+f"(d[16]),"+f"(d[17]),"+f"(d[18]),"+f"(d[19]),"+f"(d[20]),"+f"(d[21]),"+f"(d[22]),"+f"(d[23]),"+f"(d[24]),"+f"(d[25]),"+f"(d[26]),"+f"(d[27]),"+f"(d[28]),"+f"(d[29]),"+f"(d[30]),"+f"(d[31]),"+f"(d[32]),"+f"(d[33]),"+f"(d[34]),"+f"(d[35]),"+f"(d[36]),"+f"(d[37]),"+f"(d[38]),"+f"(d[39]),"+f"(d[40]),"+f"(d[41]),"+f"(d[42]),"+f"(d[43]),"+f"(d[44]),"+f"(d[45]),"+f"(d[46]),"+f"(d[47]),"+f"(d[48]),"+f"(d[49]),"+f"(d[50]),"+f"(d[51]),"+f"(d[52]),"+f"(d[53]),"+f"(d[54]),"+f"(d[55]),"+f"(d[56]),"+f"(d[57]),"+f"(d[58]),"+f"(d[59]),"+f"(d[60]),"+f"(d[61]),"+f"(d[62]),"+f"(d[63]),"+f"(d[64]),"+f"(d[65]),"+f"(d[66]),"+f"(d[67]),"+f"(d[68]),"+f"(d[69]),"+f"(d[70]),"+f"(d[71]),"+f"(d[72]),"+f"(d[73]),"+f"(d[74]),"+f"(d[75]),"+f"(d[76]),"+f"(d[77]),"+f"(d[78]),"+f"(d[79]),"+f"(d[80]),"+f"(d[81]),"+f"(d[82]),"+f"(d[83]),"+f"(d[84]),"+f"(d[85]),"+f"(d[86]),"+f"(d[87]),"+f"(d[88]),"+f"(d[89]),"+f"(d[90]),"+f"(d[91]),"+f"(d[92]),"+f"(d[93]),"+f"(d[94]),"+f"(d[95]) : "l"(da), "l"(db), "r"(sc));
}
__device__ __forceinline__ void wgmma_ss_tb_n160(float* d, uint64_t da, uint64_t db, int sc) {
  asm volatile("{.reg .pred p; setp.ne.b32 p, %82, 0;\n"
   "wgmma.mma_async.sync.aligned.m64n160k16.f32.bf16.bf16 {%0,%1,%2,%3,%4,%5,%6,%7,%8,%9,%10,%11,%12,%13,%14,%15,%16,%17,%18,%19,%20,%21,%22,%23,%24,%25,%26,%27,%28,%29,%30,%31,%32,%33,%34,%35,%36,%37,%38,%39,%40,%41,%42,%43,%44,%45,%46,%47,%48,%49,%50,%51,%52,%53,%54,%55,%56,%57,%58,%59,%60,%61,%62,%63,%64,%65,%66,%67,%68,%69,%70,%71,%72,%73,%74,%75,%76,%77,%78,%79}, %80, %81, p, 1, 1, 0, 1;}\n"
   : "+f"(d[0]),"+f"(d[1]),"+f"(d[2]),"+f"(d[3]),"+f"(d[4]),"+f"(d[5]),"+f"(d[6]),"+f"(d[7]),"+f"(d[8]),"+f"(d[9]),"+f"(d[10]),"+f"(d[11]),"+f"(d[12]),"+f"(d[13]),"+f"(d[14]),"+f"(d[15]),"+f"(d[16]),"+f"(d[17]),"+f"(d[18]),"+f"(d[19]),"+f"(d[20]),"+f"(d[21]),"+f"(d[22]),"+f"(d[23]),"+f"(d[24]),"+f"(d[25]),"+f"(d[26]),"+f"(d[27]),"+f"(d[28]),"+f"(d[29]),"+f"(d[30]),"+f"(d[31]),"+f"(d[32]),"+f"(d[33]),"+f"(d[34]),"+f"(d[35]),"+f"(d[36]),"+f"(d[37]),"+f"(d[38]),"+f"(d[39]),"+f"(d[40]),"+f"(d[41]),"+f"(d[42]),"+f"(d[43]),"+f"(d[44]),"+f"(d[45]),"+f"(d[46]),"+f"(d[47]),"+f"(d[48]),"+f"(d[49]),"+f"(d[50]),"+f"(d[51]),"+f"(d[52]),"+f"(d[53]),"+f"(d[54]),"+f"(d[55]),"+f"(d[56]),"+f"(d[57]),"+f"(d[58]),"+f"(d[59]),"+f"(d[60]),"+f"(d[61]),"+f"(d[62]),"+f"(d[63]),"+f"(d[64]),"+f"(d[65]),"+f"(d[66]),"+f"(d[67]),"+f"(d[68]),"+f"(d[69]),"+f"(d[70]),"+f"(d[71]),"+f"(d[72]),"+f"(d[73]),"+f"(d[74]),"+f"(d[75]),"+f"(d[76]),"+f"(d[77]),"+f"(d[78]),"+f"(d[79]) : "l"(da), "l"(db), "r"(sc));
}
__device__ __forceinline__ void wgmma_rs_tb_n192(float* d, const uint4& a, uint64_t db, int sc) {
  asm volatile("{.reg .pred p; setp.ne.b32 p, %101, 0;\n"
   "wgmma.mma_async.sync.aligned.m64n192k16.f32.bf16.bf16 {%0,%1,%2,%3,%4,%5,%6,%7,%8,%9,%10,%11,%12,%13,%14,%15,%16,%17,%18,%19,%20,%21,%22,%23,%24,%25,%26,%27,%28,%29,%30,%31,%32,%33,%34,%35,%36,%37,%38,%39,%40,%41,%42,%43,%44,%45,%46,%47,%48,%49,%50,%51,%52,%53,%54,%55,%56,%57,%58,%59,%60,%61,%62,%63,%64,%65,%66,%67,%68,%69,%70,%71,%72,%73,%74,%75,%76,%77,%78,%79,%80,%81,%82,%83,%84,%85,%86,%87,%88,%89,%90,%91,%92,%93,%94,%95}, {%96,%97,%98,%99}, %100, p, 1, 1, 1;}\n"
   : "+f"(d[0]),"+f"(d[1]),"+f"(d[2]),"+f"(d[3]),"+f"(d[4]),"+f"(d[5]),"+f"(d[6]),"+f"(d[7]),"+f"(d[8]),"+f"(d[9]),"+f"(d[10]),"+f"(d[11]),"+f"(d[12]),"+f"(d[13]),"+f"(d[14]),"+f"(d[15]),"+f"(d[16]),"+f"(d[17]),"+f"(d[18]),"+f"(d[19]),"+f"(d[20]),"+f"(d[21]),"+f"(d[22]),"+f"(d[23]),"+f"(d[24]),"+f"(d[25]),"+f"(d[26]),"+f"(d[27]),"+f"(d[28]),"+f"(d[29]),"+f"(d[30]),"+f"(d[31]),"+f"(d[32]),"+f"(d[33]),"+f"(d[34]),"+f"(d[35]),"+f"(d[36]),"+f"(d[37]),"+f"(d[38]),"+f"(d[39]),"+f"(d[40]),"+f"(d[41]),"+f"(d[42]),"+f"(d[43]),"+f"(d[44]),"+f"(d[45]),"+f"(d[46]),"+f"(d[47]),"+f"(d[48]),"+f"(d[49]),"+f"(d[50]),"+f"(d[51]),"+f"(d[52]),"+f"(d[53]),"+f"(d[54]),"+f"(d[55]),"+f"(d[56]),"+f"(d[57]),"+f"(d[58]),"+f"(d[59]),"+f"(d[60]),"+f"(d[61]),"+f"(d[62]),"+f"(d[63]),"+f"(d[64]),"+f"(d[65]),"+f"(d[66]),"+f"(d[67]),"+f"(d[68]),"+f"(d[69]),"+f"(d[70]),"+f"(d[71]),"+f"(d[72]),"+f"(d[73]),"+f"(d[74]),"+f"(d[75]),"+f"(d[76]),"+f"(d[77]),"+f"(d[78]),"+f"(d[79]),"+f"(d[80]),"+f"(d[81]),"+f"(d[82]),"+f"(d[83]),"+f"(d[84]),"+f"(d[85]),"+f"(d[86]),"+f"(d[87]),"+f"(d[88]),"+f"(d[89]),"+f"(d[90]),"+f"(d[91]),"+f"(d[92]),"+f"(d[93]),"+f"(d[94]),"+f"(d[95]) : "r"(a.x), "r"(a.y), "r"(a.z), "r"(a.w), "l"(db), "r"(sc));
}
template<int N> __device__ __forceinline__ void wgmma_rs(float* d, const uint32_t* a, uint64_t db, int sc);
template<> __device__ __forceinline__ void wgmma_rs<128>(float* d, const uint32_t* a, uint64_t db, int sc) {
  asm volatile("{.reg .pred p; setp.ne.b32 p, %69, 0;\n"
   "wgmma.mma_async.sync.aligned.m64n128k16.f32.bf16.bf16 {%0,%1,%2,%3,%4,%5,%6,%7,%8,%9,%10,%11,%12,%13,%14,%15,%16,%17,%18,%19,%20,%21,%22,%23,%24,%25,%26,%27,%28,%29,%30,%31,%32,%33,%34,%35,%36,%37,%38,%39,%40,%41,%42,%43,%44,%45,%46,%47,%48,%49,%50,%51,%52,%53,%54,%55,%56,%57,%58,%59,%60,%61,%62,%63}, {%64,%65,%66,%67}, %68, p, 1, 1, 0;}\n"
   : "+f"(d[0]),"+f"(d[1]),"+f"(d[2]),"+f"(d[3]),"+f"(d[4]),"+f"(d[5]),"+f"(d[6]),"+f"(d[7]),"+f"(d[8]),"+f"(d[9]),"+f"(d[10]),"+f"(d[11]),"+f"(d[12]),"+f"(d[13]),"+f"(d[14]),"+f"(d[15]),"+f"(d[16]),"+f"(d[17]),"+f"(d[18]),"+f"(d[19]),"+f"(d[20]),"+f"(d[21]),"+f"(d[22]),"+f"(d[23]),"+f"(d[24]),"+f"(d[25]),"+f"(d[26]),"+f"(d[27]),"+f"(d[28]),"+f"(d[29]),"+f"(d[30]),"+f"(d[31]),"+f"(d[32]),"+f"(d[33]),"+f"(d[34]),"+f"(d[35]),"+f"(d[36]),"+f"(d[37]),"+f"(d[38]),"+f"(d[39]),"+f"(d[40]),"+f"(d[41]),"+f"(d[42]),"+f"(d[43]),"+f"(d[44]),"+f"(d[45]),"+f"(d[46]),"+f"(d[47]),"+f"(d[48]),"+f"(d[49]),"+f"(d[50]),"+f"(d[51]),"+f"(d[52]),"+f"(d[53]),"+f"(d[54]),"+f"(d[55]),"+f"(d[56]),"+f"(d[57]),"+f"(d[58]),"+f"(d[59]),"+f"(d[60]),"+f"(d[61]),"+f"(d[62]),"+f"(d[63]) : "r"(a[0]), "r"(a[1]), "r"(a[2]), "r"(a[3]), "l"(db), "r"(sc));
}
template<> __device__ __forceinline__ void wgmma_rs<96>(float* d, const uint32_t* a, uint64_t db, int sc) {
  asm volatile("{.reg .pred p; setp.ne.b32 p, %53, 0;\n"
   "wgmma.mma_async.sync.aligned.m64n96k16.f32.bf16.bf16 {%0,%1,%2,%3,%4,%5,%6,%7,%8,%9,%10,%11,%12,%13,%14,%15,%16,%17,%18,%19,%20,%21,%22,%23,%24,%25,%26,%27,%28,%29,%30,%31,%32,%33,%34,%35,%36,%37,%38,%39,%40,%41,%42,%43,%44,%45,%46,%47}, {%48,%49,%50,%51}, %52, p, 1, 1, 0;}\n"
   : "+f"(d[0]),"+f"(d[1]),"+f"(d[2]),"+f"(d[3]),"+f"(d[4]),"+f"(d[5]),"+f"(d[6]),"+f"(d[7]),"+f"(d[8]),"+f"(d[9]),"+f"(d[10]),"+f"(d[11]),"+f"(d[12]),"+f"(d[13]),"+f"(d[14]),"+f"(d[15]),"+f"(d[16]),"+f"(d[17]),"+f"(d[18]),"+f"(d[19]),"+f"(d[20]),"+f"(d[21]),"+f"(d[22]),"+f"(d[23]),"+f"(d[24]),"+f"(d[25]),"+f"(d[26]),"+f"(d[27]),"+f"(d[28]),"+f"(d[29]),"+f"(d[30]),"+f"(d[31]),"+f"(d[32]),"+f"(d[33]),"+f"(d[34]),"+f"(d[35]),"+f"(d[36]),"+f"(d[37]),"+f"(d[38]),"+f"(d[39]),"+f"(d[40]),"+f"(d[41]),"+f"(d[42]),"+f"(d[43]),"+f"(d[44]),"+f"(d[45]),"+f"(d[46]),"+f"(d[47]) : "r"(a[0]), "r"(a[1]), "r"(a[2]), "r"(a[3]), "l"(db), "r"(sc));
}
template<> __device__ __forceinline__ void wgmma_rs<64>(float* d, const uint32_t* a, uint64_t db, int sc) {
  asm volatile("{.reg .pred p; setp.ne.b32 p, %37, 0;\n"
   "wgmma.mma_async.sync.aligned.m64n64k16.f32.bf16.bf16 {%0,%1,%2,%3,%4,%5,%6,%7,%8,%9,%10,%11,%12,%13,%14,%15,%16,%17,%18,%19,%20,%21,%22,%23,%24,%25,%26,%27,%28,%29,%30,%31}, {%32,%33,%34,%35}, %36, p, 1, 1, 0;}\n"
   : "+f"(d[0]),"+f"(d[1]),"+f"(d[2]),"+f"(d[3]),"+f"(d[4]),"+f"(d[5]),"+f"(d[6]),"+f"(d[7]),"+f"(d[8]),"+f"(d[9]),"+f"(d[10]),"+f"(d[11]),"+f"(d[12]),"+f"(d[13]),"+f"(d[14]),"+f"(d[15]),"+f"(d[16]),"+f"(d[17]),"+f"(d[18]),"+f"(d[19]),"+f"(d[20]),"+f"(d[21]),"+f"(d[22]),"+f"(d[23]),"+f"(d[24]),"+f"(d[25]),"+f"(d[26]),"+f"(d[27]),"+f"(d[28]),"+f"(d[29]),"+f"(d[30]),"+f"(d[31]) : "r"(a[0]), "r"(a[1]), "r"(a[2]), "r"(a[3]), "l"(db), "r"(sc));
}
template<> __device__ __forceinline__ void wgmma_rs<32>(float* d, const uint32_t* a, uint64_t db, int sc) {
  asm volatile("{.reg .pred p; setp.ne.b32 p, %21, 0;\n"
   "wgmma.mma_async.sync.aligned.m64n32k16.f32.bf16.bf16 {%0,%1,%2,%3,%4,%5,%6,%7,%8,%9,%10,%11,%12,%13,%14,%15}, {%16,%17,%18,%19}, %20, p, 1, 1, 0;}\n"
   : "+f"(d[0]),"+f"(d[1]),"+f"(d[2]),"+f"(d[3]),"+f"(d[4]),"+f"(d[5]),"+f"(d[6]),"+f"(d[7]),"+f"(d[8]),"+f"(d[9]),"+f"(d[10]),"+f"(d[11]),"+f"(d[12]),"+f"(d[13]),"+f"(d[14]),"+f"(d[15]) : "r"(a[0]), "r"(a[1]), "r"(a[2]), "r"(a[3]), "l"(db), "r"(sc));
}

__device__ __forceinline__ void conv_dupA(uint32_t* A, uint32_t zz) {
#pragma unroll
  for (int s = 0; s < 4; s++) {
    asm volatile("xor.b32 %0, %1, %2;" : "=r"(A[4 * s + 3]) : "r"(A[4 * s]), "r"(zz));
    if (s < 3) asm volatile("xor.b32 %0, %1, %2;" : "=r"(A[4 * s + 6]) : "r"(A[4 * s + 1]), "r"(zz));
  }
}
template <int OFF, int DUP = 1> __device__ __forceinline__ void conv_ldA(uint32_t* A, uint32_t ra, uint32_t zz) {
  A[2] = lds32(ra + OFF);
#pragma unroll
  for (int s = 0; s < 4; s++) { A[4 * s] = lds32(ra + OFF + 32 * s + 16); A[4 * s + 1] = lds32(ra + OFF + 32 * s + 32); }
  if (DUP) conv_dupA(A, zz);
}
template <int N, int H, int ACC = 0> __device__ __forceinline__ void conv_grp(float* T, const uint32_t* A, uint64_t dX) {
  WG_FENCE();
#pragma unroll
  for (int s = 0; s < 4; s++) wgmma_rs<N>(T, A + 4 * s, dX - (4 * H + s), (ACC || H > 0 || s > 0));
  WG_COMMIT();
}
template <int H> __device__ __forceinline__ void conv_grp2(float* T, float* U, const uint32_t* A, uint64_t dX) {
  WG_FENCE();
#pragma unroll
  for (int s = 0; s < 4; s++) {
    wgmma_rs<64>(T, A + 4 * s, dX + 32 - (4 * H + s), (H > 0 || s > 0));
    wgmma_rs<32>(U, A + 4 * s, dX - (4 * H + s), (H > 0 || s > 0));
  }
  WG_COMMIT();
}

template <int NI, int ST> __device__ __forceinline__ void conv_reduce(uint32_t zo, uint32_t pb, uint32_t pitch, int idx, uint32_t bar) {
  const int a = idx >> 1, half = idx & 1;
  const uint32_t p0 = pb + half * 2048 + ((a ^ (half << 2)) << 4), p2 = p0 + pitch - 256;
  uint4 v[NI][4];
#pragma unroll
  for (int n = 0; n < NI; n++) {
    if (n == 2 && idx >= 64) break;
#pragma unroll
    for (int q = 0; q < 4; q++) { v[n][q] = make_uint4(0, 0, 0, 0); if (n > 0 || a >= 8 * q) v[n][q] = lds128((q < 2 ? p0 : p2) + (q & 1) * 3968 + n * ST * 8); }
    if (NI == 2 && n == 0) continue;
#pragma unroll
    for (int m = NI == 2 ? 0 : n; m <= n; m++)
      sts128(zo + idx * 16 + m * ST * 16, badd2(badd2(v[m][0].x, v[m][1].x), badd2(v[m][2].x, v[m][3].x)), badd2(badd2(v[m][0].y, v[m][1].y), badd2(v[m][2].y, v[m][3].y)),
             badd2(badd2(v[m][0].z, v[m][1].z), badd2(v[m][2].z, v[m][3].z)), badd2(badd2(v[m][0].w, v[m][1].w), badd2(v[m][2].w, v[m][3].w)));
  }
  asm volatile("fence.proxy.async.shared::cta;" ::: "memory");
  if (NI == 2) mbar_arrive(bar);
  else asm volatile("mbarrier.arrive.shared::cta.b64 _, [%0], %1;" ::"r"(bar), "r"(idx < 32 ? 2 : 1) : "memory");
}

__global__ void __launch_bounds__(384, 1) fused_kernel(const __grid_constant__ Maps maps, const Ptrs P, const uint32_t zz) {
  extern __shared__ __align__(1024) uint8_t smem[];
  constexpr uint32_t sb = 1024;
  const int tid = threadIdx.x;
  const int b = blockIdx.x;
  const uint32_t bars = sb + SM_BAR;

#define BAR(i) (bars + 8u * (i))
  TR(t63);
  const int rt = (b >> 1) & 15, ct = (b & 1) | ((b >> 5) << 1);
  const int rb = b >> 2, cb = b & 3;
  const int b2 = cb * 32 + rb;
  const int ch0 = cb * 160 + rb;

  if ((tid >> 5) == 8) {
    if (elect_one()) {
      mbar_init(BAR(B_FX), 1); mbar_init(BAR(B_FW), 1); mbar_init(BAR(B_FW + 1), 1);
      asm volatile("fence.proxy.async.shared::cta;" ::: "memory");
      mbar_expect_tx(BAR(B_FX), 16384); tma2d(sb + SM_X, &maps.x, BAR(B_FX), 0, rt * 128);
#pragma unroll
      for (int n = 0; n < NPRE; n++) {
        mbar_expect_tx(BAR(B_FW + n), 24576);
        tma3d(sb + SM_W + n * 24576, &maps.wg, BAR(B_FW + n), 0, n * 32, ct * 3); tma3d(sb + SM_W + n * 24576 + 12288, &maps.wu, BAR(B_FW + n), 0, n * 32, ct * 3);
      }
      mbar_init(BAR(B_FX + 1), 1); mbar_init(BAR(B_FX + 2), 1); mbar_init(BAR(B_FW + 2), 1);
      asm volatile("fence.proxy.async.shared::cta;" ::: "memory");
    }
  }
  const int wg = __shfl_sync(0xffffffffu, tid >> 7, 0);

  if (wg == 2) {
    asm volatile("setmaxnreg.dec.sync.aligned.u32 40;");
    bar_sync(0, 384);
    const int warp = __shfl_sync(0xffffffffu, tid >> 5, 0) - 8, lane = tid & 31;
    if (warp == 0) {
      if (elect_one()) {
        TS1(11); TW(9, t9); TW(10, t10);
#pragma unroll
        for (int n = NPRE; n < 20; n++) {
          const int k = n < 14 ? (n >> 1) : n < 17 ? n - 7 : n - 10;
          const bool up = n < 14 ? (n & 1) : (n >= 17);
          if (n == PF_N) { tma3d_prefetch(&maps.wu, 0, 576, ct * 3); tma3d_prefetch(&maps.wu, 0, 608, ct * 3); }
          if (!up && n != 16) {
            const int xs = k % 3;
            if (k >= 3) mbar_wait(BAR(B_EX + xs), ((k / 3) - 1) & 1);
            mbar_expect_tx(BAR(B_FX + xs), 16384);
            tma2d(sb + SM_X + xs * 16384, &maps.x, BAR(B_FX + xs), k * 64, rt * 128);
          }
          const int s = n % 5;
          if (n >= 5) mbar_wait(BAR(B_EW + s), ((n / 5) - 1) & 1);
          mbar_expect_tx(BAR(B_FW + s), 24576);
          tma3d(sb + SM_W + s * 24576, n >= 17 ? &maps.wu : &maps.wg, BAR(B_FW + s), 0, n < 14 ? n * 32 : k * 64, ct * 3);
          tma3d(sb + SM_W + s * 24576 + 12288, n < 14 || n >= 17 ? &maps.wu : &maps.wg, BAR(B_FW + s), 0, n < 14 ? n * 32 : k * 64 + 32, ct * 3);
          if (n == X9_N) {
            mbar_wait(BAR(B_GF), 0);
            TS1(33);
            mbar_expect_tx(BAR(B_F9), 16384);
            tma2d(sb + SM_GAP, &maps.x, BAR(B_F9), 576, rt * 128);
          }
          if (n == KV0 || n == KV1 || n == KV2 || n == KV3 || n == KV4) {
            const int r = n == KV0 ? 0 : n == KV1 ? 1 : n == KV2 ? 2 : n == KV3 ? 3 : 4;
            mbar_expect_tx(BAR(B_KV + r), 8576);
            tma3d(sb + SM_D + r * 8576, &maps.k, BAR(B_KV + r), 0, (b >> 1) * 32 - 3, (b & 1) * 10 + 2 * r);
            tma3d(sb + SM_D + r * 8576 + 4480, &maps.v, BAR(B_KV + r), 0, (b >> 1) * 32, (b & 1) * 10 + 2 * r);
          }
          if (n >= SK_N && n < SK_N + 5) l2_prefetch(P.ssm_k + (size_t)(ch0 + 32 * (n - SK_N)) * 2048, 4096);
          if (n == WD_N) {
            mbar_expect_tx(BAR(B_WD), b < 120 ? 16384 : 0);
            if (b < 120) tma3d(sb + SM_GAP, &maps.wd, BAR(B_WD), 0, (b / 5) * 64, (b % 5) * 4);
          }
        }
        TS1(32);
        mbar_wait(BAR(B_PRE), 0);
        const uint32_t target = lds32v(sb + SM_BAR + 576);
        mbar_wait(BAR(B_EW + 0), 1);
        flag_wait(&g_cnt[0], target);
        mbar_expect_tx(BAR(B_XI), 5 * XCH);
        tma3d(sb + SM_W, &maps.xl, BAR(B_XI), 0, -2, b2 * 10);
        TS1(1);
        const uint8_t* wsrc = g_wd + cb * 20480;
        mbar_wait(BAR(B_G1), 0);
        for (int s = 0; s < 4; s++) {
          mbar_expect_tx(BAR(B_F2 + s), 28672);
          bulk_g2s(sb + SM_R2 + s * 28672 + 8192, wsrc + s * 81920, 20480, BAR(B_F2 + s));
        }
        TS1(2);
        flag_wait(&g_cnt[(1 + rb) * 32], target);
        TS1(3);
        const uint8_t* hsrc = g_h + (size_t)rb * 24 * 8192;
        for (int s = 0; s < 4; s++) {
          if (!(s & 1)) mbar_wait(BAR(B_ZR + (s >> 1)), 0);
          bulk_g2s(sb + SM_R2 + s * 28672, hsrc + s * 8192, 8192, BAR(B_F2 + s));
        }
        mbar_expect_tx(BAR(B_Q), 256);
        bulk_g2s(sb + SM_GT, g_gate + rb * 64, 256, BAR(B_Q));
        for (int c = 4, s = 0, ph = 0; c < 24; c++) {
          if (c == 8) mbar_wait(BAR(B_ZR + 2), 0); else mbar_wait(BAR(B_E2 + s), s == 4 ? ph ^ 1 : ph);
          mbar_expect_tx(BAR(B_F2 + s), 28672);
          bulk_g2s(s == 4 ? sb + SM_W : sb + SM_R2 + s * 28672, hsrc + c * 8192, 8192, BAR(B_F2 + s));
          bulk_g2s(s == 4 ? sb + SM_W + 24576 : sb + SM_R2 + s * 28672 + 8192, wsrc + c * 81920, 20480, BAR(B_F2 + s));
          if (++s == 5) { s = 0; ph ^= 1; }
        }
        TS1(4);
      }
    } else {
      const int hw = warp - 1;
      if (hw == 2) {
        if (smem_u32(smem) != sb) asm volatile("trap;");
        const int c8 = lane & 7, r4 = lane >> 3;
        float acc[4] = {0.f, 0.f, 0.f, 0.f};
        uint4 gw = __ldg((const uint4*)(P.gate_w + c8 * 8));
        gw.x |= __ldg((const uint32_t*)(P.gate_w + 128 + lane * 16)) & zz;
        uint32_t xs = 0, xph = 0;
        const __nv_bfloat16* pw = (lane & 1 ? P.wu : P.wg) + (rt * 4 + (lane >> 3)) * 1536 + ct * 192 + ((lane >> 1) & 3) * 64;
        const __nv_bfloat16* px = P.x + (rt * 128 + ct * 16 + (lane & 15)) * 640;
        const bool pfw = (lane & 6) != 6;
#define PFK(kk) { if (pfw) asm volatile("prefetch.global.L2 [%0];" ::"l"(pw + (kk) * 98304)); if (lane < 16) asm volatile("prefetch.global.L2 [%0];" ::"l"(px + (kk) * 64)); }
        for (int k = PF0; k < PD; k++) PFK(k)
#pragma unroll 1
        for (int k = 0; k < 10; k++) {
          const uint4 gn = __ldg((const uint4*)(P.gate_w + (k < 9 ? k + 1 : 0) * 64 + c8 * 8));
          if (k == 9) { xs = 3; mbar_wait(BAR(B_F9), 0); } else mbar_wait(BAR(B_FX + xs), xph);
          if (k + PD < 10) PFK(k + PD)
#pragma unroll
          for (int i = 0; i < 4; i++) {
            const int row = (i >> 1) * 64 + ct * 8 + (i & 1) * 4 + r4;
            const uint4 v = lds128(sb + SM_X + xs * 16384 + row * 128 + ((c8 ^ (row & 7)) << 4));
            const uint32_t p[4] = {bmul2(v.x, gw.x), bmul2(v.y, gw.y), bmul2(v.z, gw.z), bmul2(v.w, gw.w)};
#pragma unroll
            for (int e = 0; e < 4; e++) acc[i] += __uint_as_float(p[e] << 16) + __uint_as_float(p[e] & 0xffff0000u);
          }
          __syncwarp();
          if (lane == 0 && k < 6) mbar_arrive(BAR(B_EX + xs));
          if (lane == 0 && k == WK) {
            mbar_wait(BAR(B_WD), 0);
            if (b < 120) bulk_s2g(g_wd + (size_t)b * 16384, sb + SM_GAP, 16384);
            asm volatile("cp.async.bulk.commit_group;" ::: "memory");
          }
          if (lane == 0 && k == WK + 1) {
            asm volatile("cp.async.bulk.wait_group 0;" ::: "memory");
            mbar_arrive(BAR(B_GF));
          }
          __syncwarp();
          if (++xs == 3) { xs = 0; xph ^= 1; }
          gw = gn;
        }
#pragma unroll
        for (int i = 0; i < 4; i++)
#pragma unroll
          for (int o = 1; o < 8; o <<= 1) acc[i] += __shfl_xor_sync(0xffffffffu, acc[i], o);
        if (c8 < 4) {
          const float sv = c8 == 0 ? acc[0] : c8 == 1 ? acc[1] : c8 == 2 ? acc[2] : acc[3];
          const float l = __bfloat162float(__float2bfloat16_rn(sv));
          const float gv = __bfloat162float(__float2bfloat16_rn(1.0f / (1.0f + __expf(-l))));
          asm volatile("st.shared.f32 [%0], %1;" ::"r"(sb + SM_GO + c8 * 16 + r4 * 4), "f"(gv) : "memory");
          asm volatile("fence.proxy.async.shared::cta;" ::: "memory");
        }
        __syncwarp();
        if (lane == 0) { mbar_arrive(BAR(B_G1)); mbar_arrive(BAR(B_HS + 0)); mbar_arrive(BAR(B_HS + 1)); TS1(7); }
      } else {
        const int ht = tid - 288;
        const int rc = b >> 1, chb = (b & 1) * 320;
        const int cl = hw * 32 + (lane >> 1) * 2;
        const __nv_bfloat16* skp = P.shift_k + (chb + cl) * 4;
        uint4 sk = __ldg((const uint4*)skp);
        if (ht < 20) asm volatile("prefetch.global.L2 [%0];" ::"l"(P.shift_k + chb * 4 + ht * 64));
        uint32_t ka = sb + SM_D + hw * 2240 + (lane >> 1) * 4 + (lane & 1) * 1024;
        const uint32_t vo = 4480 - hw * 192, so = 4480 - hw * 192 + (lane >> 1) * 28 - (lane & 1) * 1008;
#pragma unroll 1
        for (int pg = 0; pg < 5; pg++) {
          const uint32_t w0 = __byte_perm(sk.x, sk.z, 0x5410), w1 = __byte_perm(sk.x, sk.z, 0x7632);
          const uint32_t w2 = __byte_perm(sk.y, sk.w, 0x5410), w3 = __byte_perm(sk.y, sk.w, 0x7632);
          sk = __ldg((const uint4*)(skp + (pg < 4 ? pg + 1 : 0) * 256));
          mbar_wait(BAR(B_KV + pg), 0);
          if (ht == 0) TS1(21 + pg);
          uint32_t kk[19], o[8];
#pragma unroll
          for (int i = 0; i < 11; i++) kk[i] = lds32(ka + i * 64);
#pragma unroll
          for (int h = 0; h < 2; h++) {
#pragma unroll
            for (int i = 0; i < 8; i++) o[i] = lds32(ka + vo + (8 * h + i) * 64);
#pragma unroll
            for (int i = 0; i < 8; i++) o[i] = bmul2(bfma2(kk[8 * h + i + 3], w0, bfma2(kk[8 * h + i + 2], w1, bfma2(kk[8 * h + i + 1], w2, bmul2(kk[8 * h + i], w3)))), o[i]);
            if (h == 0) {
#pragma unroll
              for (int i = 11; i < 19; i++) kk[i] = lds32(ka + i * 64);
            }
            __syncwarp();
            sts128(ka + so + h * 512, __byte_perm(o[1], o[0], 0x5410), __byte_perm(o[3], o[2], 0x5410), __byte_perm(o[5], o[4], 0x5410), __byte_perm(o[7], o[6], 0x5410));
            sts128(ka + so + h * 512 + 1024, __byte_perm(o[1], o[0], 0x7632), __byte_perm(o[3], o[2], 0x7632), __byte_perm(o[5], o[4], 0x7632), __byte_perm(o[7], o[6], 0x7632));
          }
          asm volatile("fence.proxy.async.shared::cta;" ::: "memory");
          __syncwarp();
          if (lane == 0) {
            const int blk = (b & 1) * 10 + 2 * pg + hw;
            asm volatile("cp.async.bulk.tensor.5d.global.shared::cta.bulk_group [%0, {%2,%3,%3,%3,%4}], [%1];" ::"l"(&maps.xs), "r"(ka + vo), "r"(rc * 16), "r"(0), "r"((blk / 5) * 160 + blk % 5) : "memory");
          }
          ka += 8576;
        }
        if (lane == 0) {
          asm volatile("cp.async.bulk.commit_group;" ::: "memory");
          asm volatile("cp.async.bulk.wait_group.read 0;" ::: "memory");
        }
        bar_sync(3, 64);
        if (ht == 0) {
          TS1(12);
          mbar_expect_tx(BAR(B_HR), 20480);
          for (int c = 0; c < 5; c++) bulk_g2s(sb + SM_D + 128 + c * TP + 4128, P.ssm_k + (size_t)(ch0 + 32 * c) * 2048, 4096, BAR(B_HR));
        }
        uint32_t old = 0;
        if (lane == 0) {
          asm volatile("cp.async.bulk.wait_group 0;" ::: "memory");
          mbar_arrive(BAR(B_KD));
          if (hw) {
            TS1(6);
            mbar_wait(BAR(B_KD), 0);
            mbar_wait(BAR(B_GF), 0);
            TS1(20);
            asm volatile("atom.relaxed.gpu.global.add.u32 %0, [%1], 1;" : "=r"(old) : "l"(&g_cnt[0]) : "memory");
          }
        }
        if (lane < 20) sts128(sb + SM_D + 96 + (lane >> 2) * TP + ((lane >> 1) & 1) * 4128 + (lane & 1) * 16, 0, 0, 0, 0);
        uint32_t dv = 0;
        if (ht < 5) dv = __ldg((const unsigned short*)(P.ssm_D + ch0 + 32 * ht));
        mbar_wait(BAR(B_HR), 0);
        if (ht < 5) {
          const uint32_t a0 = sb + SM_D + 128 + 4128 + ht * TP;
          asm volatile("st.shared.u32 [%0], %1;" ::"r"(a0), "r"(badd2(lds32(a0), dv)) : "memory");
        }
        __syncwarp();
        if (ht == 32) TS1(13);
#pragma unroll 1
        for (int c = 0; c < 5; c++) {
          const uint32_t d = sb + SM_D + 128 + c * TP + hw * 2048 + lane * 16;
          uint4 v[4]; uint32_t pv[4];
#pragma unroll
          for (int i = 0; i < 4; i++) { v[i] = lds128(d + 4128 + i * 512); pv[i] = lds32(d + 4124 + i * 512); }
#pragma unroll
          for (int i = 0; i < 4; i++)
            sts128(d + i * 512, __byte_perm(pv[i], v[i].x, 0x5432), __byte_perm(v[i].x, v[i].y, 0x5432), __byte_perm(v[i].y, v[i].z, 0x5432), __byte_perm(v[i].z, v[i].w, 0x5432));
          if (c == 1 && ht == 32) { asm volatile("st.shared.u32 [%0], %1;" ::"r"(sb + SM_BAR + 576), "r"((old & ~127u) + 128u) : "memory"); mbar_arrive(BAR(B_PRE)); TS1(8); }
        }
        __syncwarp();
        if (lane == 0) {
          mbar_arrive(BAR(B_HC));
          if (hw) TS1(14);
          mbar_wait(BAR(B_HS + hw), 0);
          TS1(5 + hw * 10);
          bulk_s2g(g_h + ((size_t)(rt * 2 + hw) * 24 + ct * 3) * 8192, sb + SM_W + (1 + hw) * 24576, 24576);
          bulk_s2g(g_gate + rt * 128 + hw * 64 + ct * 8, sb + SM_GO + hw * 32, 32);
          asm volatile("cp.async.bulk.commit_group;" ::: "memory");
          asm volatile("cp.async.bulk.wait_group.read 0;" ::: "memory");
          mbar_arrive(BAR(B_HF + hw));
          asm volatile("cp.async.bulk.wait_group 0;" ::: "memory");
          flag_add_relaxed(&g_cnt[(1 + rt * 2 + hw) * 32], 16);
          TS1(26 + hw);
        }
        __syncwarp();
      }
#pragma unroll 1
      for (int c = 0; c < 4; c += 2) {
        mbar_wait(BAR(B_PF + (c >> 1)), 0);
        if (tid == 288) TS1(16 + c);
        conv_reduce<3, 96>(sb + SM_D + 128 + c * TP, c ? sb + SM_W + 24576 : sb + SM_R2, c ? 8192 : 28672, tid - 288, BAR(B_ZR + c));
        if (tid == 288) TS1(17 + c);
        if (tid == 320) {
          for (int i = c; i < c + 2; i++) {
            mbar_wait(BAR(B_ZR + i), 0);
            bulk_s2g(g_z + (size_t)(ch0 + 32 * i) * 4096, sb + SM_D + 128 + i * TP, 4096);
          }
          asm volatile("cp.async.bulk.commit_group;" ::: "memory");
          if (c == 0) {
            asm volatile("cp.async.bulk.wait_group.read 0;" ::: "memory");
            mbar_wait(BAR(B_HF), 0);
            mbar_expect_tx(BAR(B_Q), 36864);
            for (int i = 0; i < 5; i++) tma3d(i < 4 ? sb + SM_D + i * 4096 : sb + SM_W + 45056, &maps.q, BAR(B_Q), 0, rb * 64, cb * 5 + i);
          }
        }
        __syncwarp();
      }
      if (tid == 288) {
        mbar_wait(BAR(B_ZR + 4), 0);
        bulk_s2g(g_z + (size_t)(ch0 + 128) * 4096, sb + SM_D + 128 + 4 * TP, 4096);
        asm volatile("cp.async.bulk.commit_group;" ::: "memory");
        mbar_expect_tx(BAR(B_Q2), 4096);
      }
      if (tid == 288 || tid == 320) {
        uint32_t* fl = &g_cnt[(tid == 288 ? 37 : 33) * 32 + cb * 32];
        asm volatile("cp.async.bulk.wait_group 0;" ::: "memory");
        flag_add_relaxed(fl, 4);
        TS1(tid == 288 ? 30 : 28);
        flag_wait(fl, lds32v(sb + SM_BAR + 576));
        TS1(tid == 288 ? 31 : 29);
        for (int i = tid == 288 ? 4 : 0; i < (tid == 288 ? 5 : 4); i++) tma2d(sb + SM_D + 16384 + i * 4096, &maps.z, BAR(tid == 288 ? B_Q2 : B_Q), rb * 64, cb * 160 + 32 * i);
      }
    }
  } else {
    {
      uint32_t tq;
      asm volatile("mov.u32 %0, %%tid.x;" : "=r"(tq));
      const int wi = __shfl_sync(0xffffffffu, tq >> 5, 0);
      if (elect_one()) {
#pragma unroll 1
        for (int gi = wi + 1; gi < 12; gi += 8) {
          const uint32_t cnt = gi < 5 ? 1 : (uint32_t)(0x80808102040908ull >> (8 * (gi - 5))) & 0xff;
#pragma unroll
          for (int j = 0; j < 6; j++) mbar_init(BAR(gi * 6 + j), cnt);
        }
        asm volatile("fence.proxy.async.shared::cta;" ::: "memory");
      }
      __syncwarp();
    }
    bar_sync(0, 384);
    asm volatile("setmaxnreg.inc.sync.aligned.u32 232;");
    const int t128 = tid & 127, w = __shfl_sync(0xffffffffu, t128 >> 5, 0), lane = tid & 31;
    const uint32_t ra0 = sb + SM_D + 128 + (((lane >> 2) & 1) ? 4128 + 2 * (128 * w + (lane >> 2) - 2 * (lane & 3) - 9) : 2 * (128 * w + (lane >> 2) - 2 * (lane & 3) - 8));
    uint32_t A0[16], A1[16], A2[16];
    {
      float ag[96], au[96];
      const uint64_t dA0 = mkdesc(sb + SM_X + wg * 8192, 16, 1024, 1);
      const uint64_t dB0 = mkdesc(sb + SM_W, 4096, 1024, 1);
      const uint32_t xa = sb + SM_X + wg * 8192 + (16 * w + (lane & 15)) * 128 + (((lane >> 4) ^ (lane & 7)) << 4);
      uint4 A[2];
      TS(18);
      mbar_wait(BAR(B_FX + 0), 0);
      TS(19);
      A[0] = ldsm4(xa);
#pragma unroll
      for (int st = 0; st < 28; st++) {
        const int k = st >> 2, kk = st & 3, n = st >> 1, xs = k % 3;
        if (!(st & 1)) mbar_wait(BAR(B_FW + n % 5), (n / 5) & 1);
        if (LSTEP && st > 0 && st % (LSTEP + !LSTEP) == 0) bar_sync(7, 256);
        if (kk == 0) TS(20 + k);
        WG_FENCE();
        wgmma_rs_tb_n192(ag, A[st & 1], dB0 + (n % 5) * 1536 + (st & 1) * 128, st > 0);
        wgmma_rs_tb_n192(au, A[st & 1], dB0 + (n % 5) * 1536 + 768 + (st & 1) * 128, st > 0);
        WG_COMMIT();
        if (kk == 3 && k < 6 && lane == 0) mbar_arrive(BAR(B_EX + xs));
        WG_WAIT(1);
        if (!(st & 1) && st > 0 && lane == 0) mbar_arrive(BAR(B_EW + (n - 1) % 5));
        if (kk < 3) A[(kk + 1) & 1] = ldsm4((xa ^ ((kk + 1) << 5)) + xs * 16384);
        else if (k < 6) { mbar_wait(BAR(B_FX + (k + 1) % 3), ((k + 1) / 3) & 1); A[0] = ldsm4(xa + ((k + 1) % 3) * 16384); }
      }
      TS(1);
#define G1_UNITS(acc, xsl, wsl) { WG_FENCE(); _Pragma("unroll") for (int kk = 0; kk < 4; kk++) { wgmma_ss_tb_n192(acc, dA0 + (xsl) * 1024 + kk * 2, dB0 + (wsl) * 1536 + (kk >> 1) * 768 + (kk & 1) * 128, 1); if (kk == 3 - HOFF) WG_COMMIT(); } WG_COMMIT(); }
#define G1_UNIT(acc, xsl, wsl) { WG_FENCE(); _Pragma("unroll") for (int kk = 0; kk < 4; kk++) wgmma_ss_tb_n192(acc, dA0 + (xsl) * 1024 + kk * 2, dB0 + (wsl) * 1536 + (kk >> 1) * 768 + (kk & 1) * 128, 1); WG_COMMIT(); }
      mbar_wait(BAR(B_FX + 1), 0);
      mbar_wait(BAR(B_FW + 4), 0);
      if (wg) {
        WG_WAIT(0);
        if (lane == 0) mbar_arrive(BAR(B_EW + 3));
        bar_sync(4, 256);
      }
      TS(8);
      G1_UNIT(ag, 1, 4);
      WG_WAIT(1);
      if (lane == 0 && !wg) mbar_arrive(BAR(B_EW + 3));
      mbar_wait(BAR(B_FX + 2), 0);
      mbar_wait(BAR(B_FW + 0), 1);
      TS(6);
      G1_UNIT(ag, 2, 0);
      WG_WAIT(1);
      if (lane == 0) mbar_arrive(BAR(B_EW + 4));
      TS(9);
      mbar_wait(BAR(B_F9), 0);
      mbar_wait(BAR(B_FW + 1), 1);
      TS(16);
      G1_UNITS(ag, 3, 1);
      WG_WAIT(1);
      bar_arrive(4 + wg, 256);
      TS(14);
      if (lane == 0) mbar_arrive(BAR(B_EW + 0));
      WG_WAIT(0);
      if (lane == 0) mbar_arrive(BAR(B_EW + 1));
      TS(2);
      uint32_t sg[48], dep;
#define SIG(lo, hi) dep = sig_range<lo, hi>(ag, sg, zz);
      SIG(0, SG0)
      TS(15);
      mbar_wait(BAR(B_FW + 2) + dep, 1);
      mbar_wait(BAR(B_FW + 3), 1);
      bar_sync(5 + wg, 256);
      TS(17);
      WG_FENCE();
#define U1(xsl, wsl, kk) wgmma_ss_tb_n192(au, dA0 + (xsl) * 1024 + kk * 2, dB0 + ((wsl) * 1536 + (kk >> 1) * 768 + (kk & 1) * 128 + dep), 1);
#define SGC(n) ((SG0 + (n) * SG1) < 48 ? (SG0 + (n) * SG1) : 48)
      U1(1, 2, 0) U1(1, 2, 1) U1(1, 2, 2) SIG(SGC(0), SGC(1))
      U1(1, 2, 3) WG_COMMIT(); SIG(SGC(1), SGC(2))
      U1(2, 3, 0) SIG(SGC(2), SGC(3))
      U1(2, 3, 1) SIG(SGC(3), SGC(4))
      U1(2, 3, 2) SIG(SGC(4), SGC(5))
      U1(2, 3, 3) WG_COMMIT(); SIG(SGC(5), 48)
      WG_WAIT(1);
      if (lane == 0) mbar_arrive(BAR(B_EW + 2));
      TS(10);
      mbar_wait(BAR(B_FW + 4) + dep, 1);
      TS(12);
      G1_UNITS(au, 3, 4);
      mbar_wait(BAR(B_HC), 0);
      conv_ldA<0, 0>(A0, ra0 + wg * TP, zz); conv_ldA<128, 0>(A1, ra0 + wg * TP, zz);
      WG_WAIT(1);
      if (!wg) bar_arrive(6, 256);
      TS(3);
      mbar_wait(BAR(B_EW + 1 + wg), 1);
      WG_WAIT(0);
      if (lane == 0) mbar_arrive(BAR(B_G1));
      TS(4);
      const uint32_t hb = sb + SM_W + (1 + wg) * 24576 + (16 * w + (lane & 15)) * 128;
#pragma unroll
      for (int j = 0; j < 24; j += 2) {
        uint32_t p[4];
#pragma unroll
        for (int e = 0; e < 4; e++) p[e] = bmul2(sg[2 * j + e], pack_bf16(au[4 * j + 2 * e], au[4 * j + 2 * e + 1]));
        const int cc = (j & 7) + (lane >> 4);
        stsm4(hb + (j >> 3) * 8192 + ((cc ^ (lane & 7)) << 4), p[0], p[1], p[2], p[3]);
      }
      asm volatile("fence.proxy.async.shared::cta;" ::: "memory");
      mbar_arrive(BAR(B_HS + wg));
      TS(5);
    }
    {
      const uint32_t po = (w & 1) * 4096 + (lane & 8) * 256 + (8 * (lane >> 4) + ((lane & 7) ^ ((lane & 8) >> 1))) * 16;
      mbar_wait(BAR(B_XI), 0);
      const int c_end = 4 + wg;
      conv_dupA(A0, zz); conv_dupA(A1, zz);
      uint32_t pb = sb + SM_R2 + wg * 57344, pitch = 28672;
#pragma unroll 1
      for (int c = wg, cn; c < c_end; c = cn) {
        cn = c == 3 ? 4 : c + 2;
        const uint32_t ra = ra0 + c * TP;
        const uint64_t dX = mkdesc(sb + SM_W + c * XCH + 256, XP, 128, 0);
        float T0[64], T1[16], T2[32], T3[16];
        TS(27 + (c >> 1));
        conv_grp<128, 0>(T0, A0, dX);
        conv_grp<128, 1>(T0, A1, dX);
        conv_ldA<3072>(A2, ra, zz);
        conv_grp<32, 0>(T3, A2, dX);
        WG_WAIT(2); conv_ldA<3072 + 128>(A0, ra, zz);
        conv_grp<32, 1>(T3, A0, dX);
        WG_WAIT(2); conv_ldA<1024>(A1, ra, zz);
        conv_grp2<0>(T2, T1, A1, dX);
        WG_WAIT(2); conv_ldA<1024 + 128>(A2, ra, zz);
        conv_grp2<1>(T2, T1, A2, dX);
        WG_WAIT(2); conv_ldA<2048>(A0, ra, zz);
        conv_grp<64, 0, 1>(T2, A0, dX);
#pragma unroll
        for (int i = 0; i < 16; i++) fadd_v(T0[48 + i], T3[i]);
        WG_WAIT(2); conv_ldA<2048 + 128>(A1, ra, zz);
        conv_grp<64, 1>(T2, A1, dX);
        WG_WAIT(2);
#pragma unroll
        for (int i = 0; i < 16; i++) fadd_v(T0[16 + i], T1[i]);
        const uint32_t rn = cn < c_end ? ra0 + cn * TP : ra;
        WG_WAIT(1); conv_ldA<0>(A0, rn, zz);
        mbar_wait(BAR(c < 2 ? B_G1 : c == 4 ? B_ZR + 3 : B_HF + wg), 0);
        const uint32_t pa = pb + po + (w >> 1) * pitch;
#pragma unroll
        for (int j = 0; j < 8; j += 2)
          stsm4t(pa + j * 128, pack_bf16(T0[4 * j], T0[4 * j + 1]), pack_bf16(T0[4 * j + 2], T0[4 * j + 3]), pack_bf16(T0[4 * j + 4], T0[4 * j + 5]), pack_bf16(T0[4 * j + 6], T0[4 * j + 7]));
        WG_WAIT(0); conv_ldA<128>(A1, rn, zz);
        TS(30 + (c >> 1));
#pragma unroll
        for (int i = 0; i < 32; i++) T0[32 + i] += T2[i];
#pragma unroll
        for (int j = 8; j < 16; j += 2)
          stsm4t(pa + j * 128, pack_bf16(T0[4 * j], T0[4 * j + 1]), pack_bf16(T0[4 * j + 2], T0[4 * j + 3]), pack_bf16(T0[4 * j + 4], T0[4 * j + 5]), pack_bf16(T0[4 * j + 6], T0[4 * j + 7]));
        if (wg) {
          bar_sync(2, 128);
          conv_reduce<2, 128>(sb + SM_D + 128 + c * TP, pb, pitch, t128, BAR(B_ZR + c));
          TS(33 + (c >> 1));
        } else mbar_arrive(BAR(B_PF + (c >> 1)));
        pb = sb + SM_W + (1 + wg) * 24576; pitch = 8192;
      }
      TS(7);
    }
    const int g = lane >> 2;
    const int frow = 16 * w + (lane & 7) + 8 * ((lane >> 3) & 1);
    const uint32_t fo = frow * 64 + (((lane >> 4) ^ ((frow >> 1) & 3)) << 4);
    const uint32_t og = sb + SM_W + 2 * 24576;
    if (wg == 0) {
      float acc[80];
      const uint64_t dA0 = mkdesc(sb + SM_R2, 16, 1024, 1), dA4 = mkdesc(sb + SM_W, 16, 1024, 1);
      const uint64_t dB0 = mkdesc(sb + SM_R2 + 8192, 4096, 512, 2), dB4 = mkdesc(sb + SM_W + 24576, 4096, 512, 2);
      mbar_wait(BAR(B_F2), 0);
      bool pend = false;
      int s = 0, ph = 0, sp = 0;
#pragma unroll 1
      for (int c = 0; c < 24; c++) {
        const uint64_t dA = s == 4 ? dA4 : dA0 + s * 1792, dB = s == 4 ? dB4 : dB0 + s * 1792;
        TS(36 + (c >> 1));
        WG_FENCE();
#pragma unroll
        for (int kk = 0; kk < 4; kk++) wgmma_ss_tb_n160(acc, dA + kk * 2, dB + kk * 64, kk > 0 || c > 0);
        WG_COMMIT();
        if (pend) { WG_WAIT(1); if (lane == 0) mbar_arrive(BAR(B_E2 + sp)); }
        if (c == 23) break;
        sp = s;
        if (++s == 5 || c == 3) { s = 0; ph ^= 1; }
        const int pf = s == 4 ? ph ^ 1 : ph;
        pend = __all_sync(0xffffffffu, mbar_test(BAR(B_F2 + s), pf));
        if (!pend) {
          WG_WAIT(0);
          if (lane == 0) mbar_arrive(BAR(B_E2 + sp));
          mbar_wait(BAR(B_F2 + s), pf);
        }
      }
      TS(11);
      mbar_wait(BAR(B_GA), 0);
      uint4 ga[10];
#pragma unroll
      for (int j = 0; j < 10; j++) ga[j] = ldsm4(og + (j >> 1) * 4096 + (fo ^ ((j & 1) << 5)));
      const float gv0 = __uint_as_float(lds32(sb + SM_GT + (16 * w + g) * 4)), gv1 = __uint_as_float(lds32(sb + SM_GT + (16 * w + g + 8) * 4));
      const uint32_t om0 = pack_bf16(1.0f - gv0, 1.0f - gv0), om1 = pack_bf16(1.0f - gv1, 1.0f - gv1);
      WG_WAIT(0);
      TS(12);
#pragma unroll
      for (int j = 0; j < 10; j++) {
        const uint32_t o0 = badd2(ga[j].x, bmul2(om0, pack_bf16(acc[8 * j + 0], acc[8 * j + 1])));
        const uint32_t o1 = badd2(ga[j].y, bmul2(om1, pack_bf16(acc[8 * j + 2], acc[8 * j + 3])));
        const uint32_t o2 = badd2(ga[j].z, bmul2(om0, pack_bf16(acc[8 * j + 4], acc[8 * j + 5])));
        const uint32_t o3 = badd2(ga[j].w, bmul2(om1, pack_bf16(acc[8 * j + 6], acc[8 * j + 7])));
        stsm4(og + (j >> 1) * 4096 + (fo ^ ((j & 1) << 5)), o0, o1, o2, o3);
      }
      asm volatile("fence.proxy.async.shared::cta;" ::: "memory");
      bar_sync(1, 128);
      if (t128 == 0) {
        tma3d_store(&maps.o, og, 0, rb * 64, cb * 5);
        asm volatile("cp.async.bulk.commit_group;" ::: "memory");
        asm volatile("cp.async.bulk.wait_group.read 0;" ::: "memory");
      }
      TS(13);
    } else {
      const uint32_t za = sb + SM_D + 16384 + ((lane & 7) + 8 * (lane >> 4)) * 128 + (((2 * w + ((lane >> 3) & 1)) ^ (lane & 7)) << 4);
      mbar_wait(BAR(B_ZR + 4), 0);
      mbar_wait(BAR(B_Q), 0);
      TS(10);
      uint4 zr[10], qr[10];
#pragma unroll
      for (int j = 0; j < 10; j++) { if (j < 8) zr[j] = ldsm4t(za + j * 2048); qr[j] = ldsm4(sb + (j < 8 ? SM_D + (j >> 1) * 4096 : SM_W + 45056) + (fo ^ ((j & 1) << 5))); }
      const float gv0 = __uint_as_float(lds32(sb + SM_GT + (16 * w + g) * 4)), gv1 = __uint_as_float(lds32(sb + SM_GT + (16 * w + g + 8) * 4));
      const uint32_t g0 = pack_bf16(gv0, gv0), g1 = pack_bf16(gv1, gv1);
#pragma unroll
      for (int j = 0; j < 10; j++) {
        if (j == 8) { mbar_wait(BAR(B_Q2), 0); TS(11); zr[8] = ldsm4t(za + 8 * 2048); zr[9] = ldsm4t(za + 9 * 2048); }
        stsm4(og + (j >> 1) * 4096 + (fo ^ ((j & 1) << 5)), bmul2(g0, bmul2(qr[j].x, zr[j].x)), bmul2(g1, bmul2(qr[j].y, zr[j].y)), bmul2(g0, bmul2(qr[j].z, zr[j].z)), bmul2(g1, bmul2(qr[j].w, zr[j].w)));
      }
      mbar_arrive(BAR(B_GA));
      TS(13);
    }
  }
}

typedef CUresult (*EncFn)(CUtensorMap*, CUtensorMapDataType, cuuint32_t, void*, const cuuint64_t*, const cuuint64_t*, const cuuint32_t*, const cuuint32_t*,
                          CUtensorMapInterleave, CUtensorMapSwizzle, CUtensorMapL2promotion, CUtensorMapFloatOOBfill);

void enc(EncFn fn, CUtensorMap* m, CUtensorMapDataType dt, int rank, const void* p, const cuuint64_t* gd, const cuuint64_t* gs, const cuuint32_t* bd, CUtensorMapSwizzle sw) {
  cuuint32_t es[5] = {1, 1, 1, 1, 1};
  fn(m, dt, rank, (void*)p, gd, gs, bd, es, CU_TENSOR_MAP_INTERLEAVE_NONE, sw, CU_TENSOR_MAP_L2_PROMOTION_L2_128B, CU_TENSOR_MAP_FLOAT_OOB_FILL_NONE);
}

}

extern "C" void kernel_launch(void* const* d_in, const int* in_sizes, int n_in, void* d_out, int out_size) {
  static EncFn fn = nullptr;
  static void *zp = nullptr, *xp = nullptr;
  if (!fn) {
    cudaGetSymbolAddress(&zp, g_z);
    cudaGetSymbolAddress(&xp, g_X);
    void* f = nullptr; cudaDriverEntryPointQueryResult qr;
    cudaGetDriverEntryPoint("cuTensorMapEncodeTiled", &f, cudaEnableDefault, &qr);
    fn = (EncFn)f;
    cudaFuncSetAttribute(fused_kernel, cudaFuncAttributeMaxDynamicSharedMemorySize, SM_TOTAL);
  }
  Maps m;
  const CUtensorMapDataType BF = CU_TENSOR_MAP_DATA_TYPE_BFLOAT16;
  { cuuint64_t gd[2] = {640, 2048}, gs[1] = {1280}; cuuint32_t bd[2] = {64, 128}; enc(fn, &m.x, BF, 2, d_in[0], gd, gs, bd, CU_TENSOR_MAP_SWIZZLE_128B); }
  { cuuint64_t gd[3] = {64, 640, 24}, gs[2] = {3072, 128}; cuuint32_t bd[3] = {64, 32, 3};
    enc(fn, &m.wg, BF, 3, d_in[7], gd, gs, bd, CU_TENSOR_MAP_SWIZZLE_128B); enc(fn, &m.wu, BF, 3, d_in[8], gd, gs, bd, CU_TENSOR_MAP_SWIZZLE_128B); }
  { cuuint64_t gd[3] = {32, 1536, 20}, gs[2] = {1280, 64}; cuuint32_t bd[3] = {32, 64, 4}; enc(fn, &m.wd, BF, 3, d_in[9], gd, gs, bd, CU_TENSOR_MAP_SWIZZLE_64B); }
  { cuuint64_t gd[3] = {32, 2048, 20}, gs[2] = {1280, 64}; cuuint32_t bk[3] = {32, 35, 2}, bv[3] = {32, 32, 2};
    enc(fn, &m.k, BF, 3, d_in[1], gd, gs, bk, CU_TENSOR_MAP_SWIZZLE_NONE); enc(fn, &m.v, BF, 3, d_in[2], gd, gs, bv, CU_TENSOR_MAP_SWIZZLE_NONE); }
  { cuuint64_t gd[5] = {1024, 16, 2, 2, 485}, gs[4] = {40960, 2048, 20480, 4096}; cuuint32_t bd[5] = {16, 16, 2, 2, 1}; enc(fn, &m.xs, BF, 5, xp, gd, gs, bd, CU_TENSOR_MAP_SWIZZLE_NONE); }
  { cuuint64_t gd[3] = {64, 16, 1280}, gs[2] = {128, 2048}; cuuint32_t bd[3] = {64, 18, 10}; enc(fn, &m.xl, BF, 3, xp, gd, gs, bd, CU_TENSOR_MAP_SWIZZLE_NONE); }
  { cuuint64_t gd[3] = {32, 2048, 20}, gs[2] = {1280, 64}; cuuint32_t bd[3] = {32, 64, 5}, bq[3] = {32, 64, 1};
    enc(fn, &m.q, BF, 3, d_in[0], gd, gs, bq, CU_TENSOR_MAP_SWIZZLE_64B); enc(fn, &m.o, BF, 3, d_out, gd, gs, bd, CU_TENSOR_MAP_SWIZZLE_64B); }
  { cuuint64_t gd[2] = {2048, 640}, gs[1] = {4096}; cuuint32_t bd[2] = {64, 32}; enc(fn, &m.z, BF, 2, zp, gd, gs, bd, CU_TENSOR_MAP_SWIZZLE_128B); }
  Ptrs p;
  p.x = (const __nv_bfloat16*)d_in[0]; p.shift_k = (const __nv_bfloat16*)d_in[3]; p.ssm_k = (const __nv_bfloat16*)d_in[4];
  p.ssm_D = (const __nv_bfloat16*)d_in[5]; p.gate_w = (const __nv_bfloat16*)d_in[10];
  p.wg = (const __nv_bfloat16*)d_in[7]; p.wu = (const __nv_bfloat16*)d_in[8];
  fused_kernel<<<128, 384, SM_TOTAL, cudaStreamPerThread>>>(m, p, 0u);
}
```

```cpp
#include <cuda_runtime.h>
#include <cuda_bf16.h>
#include <cuda.h>
#include <stdint.h>

namespace {

constexpr int XP = 2304;
constexpr int XCH = 2 * XP;
constexpr int TP = 8320;
#define KV0 3
#define KV1 4
#define KV2 5
#define KV3 6
#define KV4 7
#define NPRE 1
#define PD 10
#define PF0 10
#define LSTEP 0
#define WD_N 8
#define SK_N 9
#define MAP1 1
#define MAP2 1
#define SGB 8
#define HOFF 2
#define PF_N 14
#define X9_N 15
#define WK 5
#define SG0 40
#define QC 1
#define G2P 2
#define RP0 1
#define RP1 4
#define RP2 7
#define RQ0 1
#define RQ1 3
#define RQ2 6
#define SG1 4

constexpr uint32_t SM_W = 0;
constexpr uint32_t SM_X = 122880;
constexpr uint32_t SM_R2 = 73728;
constexpr uint32_t SM_D = 188416;
constexpr uint32_t SM_BAR = 231296;
constexpr uint32_t SM_GAP = 172032;
constexpr uint32_t SM_GT = SM_BAR + 592;
constexpr uint32_t SM_GO = SM_GT + 256;
constexpr uint32_t SM_TOTAL = SM_GO + 64;
enum { B_FX = 0  , B_FW = 3  , B_KV = 8  , B_F2 = 13  , B_WD = 18, B_XI = 19, B_HR = 20, B_HF = 21  , B_Q2 = 23, B_F9 = 24, B_GF = 25, B_PRE = 26,
       B_EW = 30  , B_EX = 36  , B_G1 = 39, B_E2 = 42  , B_HC = 48, B_Q = 49, B_KD = 50, B_HS = 54  , B_ZR = 60  , B_GA = 65, B_PF = 66   };

__device__ __align__(1024) uint8_t g_X[640 * 4096];
__device__ __align__(1024) uint8_t g_h[2048 * 1536 * 2];
__device__ __align__(1024) uint8_t g_wd[1536 * 640 * 2];
__device__ __align__(1024) uint8_t g_z[640 * 4096];
__device__ __align__(1024) float g_gate[2048];
__device__ uint32_t g_cnt[44 * 32];
#define TS(i)
#define TS1(i)
#define TR(v)
#define TW(i, v)

struct Maps { CUtensorMap x, wg, wu, wd, k, v, q, o, z, xs, xl; };
struct Ptrs { uint8_t* out; const __nv_bfloat16 *x, *shift_k, *ssm_k, *ssm_D, *gate_w, *wg, *wu; };

__device__ __forceinline__ uint32_t smem_u32(const void* p) { return (uint32_t)__cvta_generic_to_shared(p); }
__device__ __forceinline__ bool elect_one() { uint32_t p; asm volatile("{.reg .pred P; elect.sync _|P, 0xffffffff; selp.u32 %0, 1, 0, P;}" : "=r"(p)); return p; }
__device__ __forceinline__ void mbar_init(uint32_t bar, uint32_t cnt) { asm volatile("mbarrier.init.shared::cta.b64 [%0], %1;" ::"r"(bar), "r"(cnt)); }
__device__ __forceinline__ void mbar_expect_tx(uint32_t bar, uint32_t bytes) { asm volatile("mbarrier.arrive.expect_tx.shared::cta.b64 _, [%0], %1;" ::"r"(bar), "r"(bytes) : "memory"); }
__device__ __forceinline__ void mbar_arrive(uint32_t bar) { asm volatile("mbarrier.arrive.shared::cta.b64 _, [%0];" ::"r"(bar) : "memory"); }
__device__ __forceinline__ void mbar_wait(uint32_t bar, uint32_t parity) {
  uint32_t ok;
  asm volatile("{.reg .pred p; mbarrier.try_wait.parity.shared::cta.b64 p, [%1], %2; selp.u32 %0,1,0,p;}" : "=r"(ok) : "r"(bar), "r"(parity) : "memory");
  if (!ok) {
    uint32_t it = 0;
    do {
      asm volatile("{.reg .pred p; mbarrier.try_wait.parity.shared::cta.b64 p, [%1], %2, 2000; selp.u32 %0,1,0,p;}" : "=r"(ok) : "r"(bar), "r"(parity) : "memory");
    } while (!ok && ++it < 100000u);
  }
}
__device__ __forceinline__ void flag_wait(const uint32_t* p, uint32_t target) {
  uint32_t v, it = 0;
  while (true) {
    asm volatile("ld.acquire.gpu.global.u32 %0, [%1];" : "=r"(v) : "l"(p) : "memory");
    if ((int)(v - target) >= 0) break;
    if (++it > 400000u) break;
    __nanosleep(20);
  }
  asm volatile("fence.proxy.async.global;" ::: "memory");
}
__device__ __forceinline__ void flag_add(uint32_t* p, uint32_t v) {
  asm volatile("red.release.gpu.global.add.u32 [%0], %1;" ::"l"(p), "r"(v) : "memory");
}
__device__ __forceinline__ void flag_add_relaxed(uint32_t* p, uint32_t v) {
  asm volatile("red.relaxed.gpu.global.add.u32 [%0], %1;" ::"l"(p), "r"(v) : "memory");
}
__device__ __forceinline__ bool mbar_test(uint32_t bar, uint32_t parity) {
  uint32_t ok;
  asm volatile("{.reg .pred p; mbarrier.test_wait.parity.shared::cta.b64 p, [%1], %2; selp.u32 %0,1,0,p;}" : "=r"(ok) : "r"(bar), "r"(parity) : "memory");
  return ok;
}
__device__ __forceinline__ void cp_async16(uint32_t dst, const void* src) { asm volatile("cp.async.cg.shared.global [%0], [%1], 16;" ::"r"(dst), "l"(src) : "memory"); }
__device__ __forceinline__ void tma2d(uint32_t dst, const CUtensorMap* m, uint32_t bar, int c0, int c1) {
  asm volatile("cp.async.bulk.tensor.2d.shared::cluster.global.mbarrier::complete_tx::bytes [%0], [%1, {%3,%4}], [%2];" ::"r"(dst), "l"(m), "r"(bar), "r"(c0), "r"(c1) : "memory");
}
__device__ __forceinline__ void tma3d(uint32_t dst, const CUtensorMap* m, uint32_t bar, int c0, int c1, int c2) {
  asm volatile("cp.async.bulk.tensor.3d.shared::cluster.global.mbarrier::complete_tx::bytes [%0], [%1, {%3,%4,%5}], [%2];" ::"r"(dst), "l"(m), "r"(bar), "r"(c0), "r"(c1), "r"(c2) : "memory");
}
__device__ __forceinline__ void tma3d_store(const CUtensorMap* m, uint32_t src, int c0, int c1, int c2) {
  asm volatile("cp.async.bulk.tensor.3d.global.shared::cta.bulk_group [%0, {%2,%3,%4}], [%1];" ::"l"(m), "r"(src), "r"(c0), "r"(c1), "r"(c2) : "memory");
}
__device__ __forceinline__ void bulk_g2s(uint32_t dst, const void* src, uint32_t bytes, uint32_t bar) {
  asm volatile("cp.async.bulk.shared::cluster.global.mbarrier::complete_tx::bytes [%0], [%1], %2, [%3];" ::"r"(dst), "l"(src), "r"(bytes), "r"(bar) : "memory");
}
__device__ __forceinline__ void bulk_s2g(void* dst, uint32_t src, uint32_t bytes) {
  asm volatile("cp.async.bulk.global.shared::cta.bulk_group [%0], [%1], %2;" ::"l"(dst), "r"(src), "r"(bytes) : "memory");
}
__device__ __forceinline__ void l2_prefetch(const void* src, uint32_t bytes) {
  asm volatile("cp.async.bulk.prefetch.L2.global [%0], %1;" ::"l"(src), "r"(bytes) : "memory");
}
__device__ __forceinline__ void tma3d_prefetch(const CUtensorMap* m, int c0, int c1, int c2) {
  asm volatile("cp.async.bulk.prefetch.tensor.3d.L2.global.tile [%0, {%1,%2,%3}];" ::"l"(m), "r"(c0), "r"(c1), "r"(c2) : "memory");
}
__device__ __forceinline__ void tmap_prefetch(const CUtensorMap* m) { asm volatile("prefetch.tensormap [%0];" ::"l"(m) : "memory"); }
__device__ __forceinline__ uint64_t mkdesc(uint32_t addr, uint32_t lbo, uint32_t sbo, uint32_t swz) {
  return (uint64_t)((addr & 0x3FFFF) >> 4) | ((uint64_t)(lbo >> 4) << 16) | ((uint64_t)(sbo >> 4) << 32) | ((uint64_t)swz << 62);
}
#define WG_FENCE() asm volatile("wgmma.fence.sync.aligned;" ::: "memory")
#define WG_COMMIT() asm volatile("wgmma.commit_group.sync.aligned;" ::: "memory")
#define WG_WAIT(n) asm volatile("wgmma.wait_group.sync.aligned " #n ";" ::: "memory")
__device__ __forceinline__ void bar_sync(int id, int n) { asm volatile("bar.sync %0, %1;" ::"r"(id), "r"(n) : "memory"); }
__device__ __forceinline__ void bar_arrive(int id, int n) { asm volatile("bar.arrive %0, %1;" ::"r"(id), "r"(n) : "memory"); }
__device__ __forceinline__ uint32_t pack_bf16(float lo, float hi) { uint32_t r; asm("cvt.rn.bf16x2.f32 %0, %1, %2;" : "=r"(r) : "f"(hi), "f"(lo)); return r; }
__device__ __forceinline__ uint32_t bmul2(uint32_t a, uint32_t b) { uint32_t r; asm("mul.rn.bf16x2 %0, %1, %2;" : "=r"(r) : "r"(a), "r"(b)); return r; }
__device__ __forceinline__ uint32_t badd2(uint32_t a, uint32_t b) { uint32_t r; asm("add.rn.bf16x2 %0, %1, %2;" : "=r"(r) : "r"(a), "r"(b)); return r; }
__device__ __forceinline__ uint32_t bfma2(uint32_t a, uint32_t b, uint32_t c) { uint32_t r; asm("fma.rn.bf16x2 %0, %1, %2, %3;" : "=r"(r) : "r"(a), "r"(b), "r"(c)); return r; }
__device__ __forceinline__ uint32_t lds32(uint32_t a) { uint32_t r; asm volatile("ld.shared.u32 %0, [%1];" : "=r"(r) : "r"(a)); return r; }
__device__ __forceinline__ uint32_t lds32v(uint32_t a) { uint32_t r; asm volatile("ld.shared.u32 %0, [%1];" : "=r"(r) : "r"(a) : "memory"); return r; }
__device__ __forceinline__ uint4 lds128(uint32_t a) { uint4 v; asm volatile("ld.shared.v4.u32 {%0,%1,%2,%3}, [%4];" : "=r"(v.x), "=r"(v.y), "=r"(v.z), "=r"(v.w) : "r"(a)); return v; }
__device__ __forceinline__ uint4 lds128m(uint32_t a) { uint4 v; asm volatile("ld.shared.v4.u32 {%0,%1,%2,%3}, [%4];" : "=r"(v.x), "=r"(v.y), "=r"(v.z), "=r"(v.w) : "r"(a) : "memory"); return v; }
__device__ __forceinline__ void sts128(uint32_t a, uint32_t x, uint32_t y, uint32_t z, uint32_t w) { asm volatile("st.shared.v4.u32 [%0], {%1,%2,%3,%4};" ::"r"(a), "r"(x), "r"(y), "r"(z), "r"(w) : "memory"); }
__device__ __forceinline__ void stsm4(uint32_t a, uint32_t x, uint32_t y, uint32_t z, uint32_t w) { asm volatile("stmatrix.sync.aligned.m8n8.x4.shared.b16 [%0], {%1,%2,%3,%4};" ::"r"(a), "r"(x), "r"(y), "r"(z), "r"(w) : "memory"); }
__device__ __forceinline__ void stsm4t(uint32_t a, uint32_t x, uint32_t y, uint32_t z, uint32_t w) { asm volatile("stmatrix.sync.aligned.m8n8.x4.trans.shared.b16 [%0], {%1,%2,%3,%4};" ::"r"(a), "r"(x), "r"(y), "r"(z), "r"(w) : "memory"); }
__device__ __forceinline__ uint4 ldsm4(uint32_t a) { uint4 v; asm volatile("ldmatrix.sync.aligned.m8n8.x4.shared.b16 {%0,%1,%2,%3}, [%4];" : "=r"(v.x), "=r"(v.y), "=r"(v.z), "=r"(v.w) : "r"(a) : "memory"); return v; }
__device__ __forceinline__ uint4 ldsm4t(uint32_t a) { uint4 v; asm volatile("ldmatrix.sync.aligned.m8n8.x4.trans.shared.b16 {%0,%1,%2,%3}, [%4];" : "=r"(v.x), "=r"(v.y), "=r"(v.z), "=r"(v.w) : "r"(a) : "memory"); return v; }
__device__ __forceinline__ void tanh_h(float& a) { asm volatile("{.reg .f32 t; mul.f32 t, %0, 0f3F000000; tanh.approx.f32 %0, t;}" : "+f"(a)); }
__device__ __forceinline__ uint32_t sig_fin(float lo, float hi, float h) {
  uint32_t r;
  asm volatile("{.reg .f32 a, b; fma.rn.f32 a, %1, %3, %3; fma.rn.f32 b, %2, %3, %3; cvt.rn.bf16x2.f32 %0, b, a;}" : "=r"(r) : "f"(lo), "f"(hi), "f"(h));
  return r;
}
template <int LO, int HI> __device__ __forceinline__ uint32_t sig_range(float* a, uint32_t* sg, uint32_t zz) {
  uint32_t dep = 0;
#pragma unroll
  for (int b = LO; b < HI; b += SGB) {
    const int e = b + SGB < HI ? b + SGB : HI;
#pragma unroll
    for (int i = 2 * b; i < 2 * e; i++) tanh_h(a[i]);
    const float h = __uint_as_float(0x3f000000u | (__float_as_uint(a[2 * e - 1]) & zz));
#pragma unroll
    for (int i = b; i < e; i++) { sg[i] = sig_fin(a[2 * i], a[2 * i + 1], h); dep |= sg[i]; }
  }
  return dep & zz;
}
__device__ __forceinline__ void fadd_v(float& a, float b) { asm volatile("add.f32 %0, %0, %1;" : "+f"(a) : "f"(b)); }

__device__ __forceinline__ void wgmma_ss_tb_n192(float* d, uint64_t da, uint64_t db, int sc) {
  asm volatile("{.reg .pred p; setp.ne.b32 p, %98, 0;\n"
   "wgmma.mma_async.sync.aligned.m64n192k16.f32.bf16.bf16 {%0,%1,%2,%3,%4,%5,%6,%7,%8,%9,%10,%11,%12,%13,%14,%15,%16,%17,%18,%19,%20,%21,%22,%23,%24,%25,%26,%27,%28,%29,%30,%31,%32,%33,%34,%35,%36,%37,%38,%39,%40,%41,%42,%43,%44,%45,%46,%47,%48,%49,%50,%51,%52,%53,%54,%55,%56,%57,%58,%59,%60,%61,%62,%63,%64,%65,%66,%67,%68,%69,%70,%71,%72,%73,%74,%75,%76,%77,%78,%79,%80,%81,%82,%83,%84,%85,%86,%87,%88,%89,%90,%91,%92,%93,%94,%95}, %96, %97, p, 1, 1, 0, 1;}\n"
   : "+f"(d[0]),"+f"(d[1]),"+f"(d[2]),"+f"(d[3]),"+f"(d[4]),"+f"(d[5]),"+f"(d[6]),"+f"(d[7]),"+f"(d[8]),"+f"(d[9]),"+f"(d[10]),"+f"(d[11]),"+f"(d[12]),"+f"(d[13]),"+f"(d[14]),"+f"(d[15]),"+f"(d[16]),"+f"(d[17]),"+f"(d[18]),"+f"(d[19]),"+f"(d[20]),"+f"(d[21]),"+f"(d[22]),"+f"(d[23]),"+f"(d[24]),"+f"(d[25]),"+f"(d[26]),"+f"(d[27]),"+f"(d[28]),"+f"(d[29]),"+f"(d[30]),"+f"(d[31]),"+f"(d[32]),"+f"(d[33]),"+f"(d[34]),"+f"(d[35]),"+f"(d[36]),"+f"(d[37]),"+f"(d[38]),"+f"(d[39]),"+f"(d[40]),"+f"(d[41]),"+f"(d[42]),"+f"(d[43]),"+f"(d[44]),"+f"(d[45]),"+f"(d[46]),"+f"(d[47]),"+f"(d[48]),"+f"(d[49]),"+f"(d[50]),"+f"(d[51]),"+f"(d[52]),"+f"(d[53]),"+f"(d[54]),"+f"(d[55]),"+f"(d[56]),"+f"(d[57]),"+f"(d[58]),"+f"(d[59]),"+f"(d[60]),"+f"(d[61]),"+f"(d[62]),"+f"(d[63]),"+f"(d[64]),"+f"(d[65]),"+f"(d[66]),"+f"(d[67]),"+f"(d[68]),"+f"(d[69]),"+f"(d[70]),"+f"(d[71]),"+f"(d[72]),"+f"(d[73]),"+f"(d[74]),"+f"(d[75]),"+f"(d[76]),"+f"(d[77]),"+f"(d[78]),"+f"(d[79]),"+f"(d[80]),"+f"(d[81]),"+f"(d[82]),"+f"(d[83]),"+f"(d[84]),"+f"(d[85]),"+f"(d[86]),"+f"(d[87]),"+f"(d[88]),"+f"(d[89]),"+f"(d[90]),"+f"(d[91]),"+f"(d[92]),"+f"(d[93]),"+f"(d[94]),"+f"(d[95]) : "l"(da), "l"(db), "r"(sc));
}
__device__ __forceinline__ void wgmma_ss_tb_n160(float* d, uint64_t da, uint64_t db, int sc) {
  asm volatile("{.reg .pred p; setp.ne.b32 p, %82, 0;\n"
   "wgmma.mma_async.sync.aligned.m64n160k16.f32.bf16.bf16 {%0,%1,%2,%3,%4,%5,%6,%7,%8,%9,%10,%11,%12,%13,%14,%15,%16,%17,%18,%19,%20,%21,%22,%23,%24,%25,%26,%27,%28,%29,%30,%31,%32,%33,%34,%35,%36,%37,%38,%39,%40,%41,%42,%43,%44,%45,%46,%47,%48,%49,%50,%51,%52,%53,%54,%55,%56,%57,%58,%59,%60,%61,%62,%63,%64,%65,%66,%67,%68,%69,%70,%71,%72,%73,%74,%75,%76,%77,%78,%79}, %80, %81, p, 1, 1, 0, 1;}\n"
   : "+f"(d[0]),"+f"(d[1]),"+f"(d[2]),"+f"(d[3]),"+f"(d[4]),"+f"(d[5]),"+f"(d[6]),"+f"(d[7]),"+f"(d[8]),"+f"(d[9]),"+f"(d[10]),"+f"(d[11]),"+f"(d[12]),"+f"(d[13]),"+f"(d[14]),"+f"(d[15]),"+f"(d[16]),"+f"(d[17]),"+f"(d[18]),"+f"(d[19]),"+f"(d[20]),"+f"(d[21]),"+f"(d[22]),"+f"(d[23]),"+f"(d[24]),"+f"(d[25]),"+f"(d[26]),"+f"(d[27]),"+f"(d[28]),"+f"(d[29]),"+f"(d[30]),"+f"(d[31]),"+f"(d[32]),"+f"(d[33]),"+f"(d[34]),"+f"(d[35]),"+f"(d[36]),"+f"(d[37]),"+f"(d[38]),"+f"(d[39]),"+f"(d[40]),"+f"(d[41]),"+f"(d[42]),"+f"(d[43]),"+f"(d[44]),"+f"(d[45]),"+f"(d[46]),"+f"(d[47]),"+f"(d[48]),"+f"(d[49]),"+f"(d[50]),"+f"(d[51]),"+f"(d[52]),"+f"(d[53]),"+f"(d[54]),"+f"(d[55]),"+f"(d[56]),"+f"(d[57]),"+f"(d[58]),"+f"(d[59]),"+f"(d[60]),"+f"(d[61]),"+f"(d[62]),"+f"(d[63]),"+f"(d[64]),"+f"(d[65]),"+f"(d[66]),"+f"(d[67]),"+f"(d[68]),"+f"(d[69]),"+f"(d[70]),"+f"(d[71]),"+f"(d[72]),"+f"(d[73]),"+f"(d[74]),"+f"(d[75]),"+f"(d[76]),"+f"(d[77]),"+f"(d[78]),"+f"(d[79]) : "l"(da), "l"(db), "r"(sc));
}
__device__ __forceinline__ void wgmma_rs_tb_n192(float* d, const uint4& a, uint64_t db, int sc) {
  asm volatile("{.reg .pred p; setp.ne.b32 p, %101, 0;\n"
   "wgmma.mma_async.sync.aligned.m64n192k16.f32.bf16.bf16 {%0,%1,%2,%3,%4,%5,%6,%7,%8,%9,%10,%11,%12,%13,%14,%15,%16,%17,%18,%19,%20,%21,%22,%23,%24,%25,%26,%27,%28,%29,%30,%31,%32,%33,%34,%35,%36,%37,%38,%39,%40,%41,%42,%43,%44,%45,%46,%47,%48,%49,%50,%51,%52,%53,%54,%55,%56,%57,%58,%59,%60,%61,%62,%63,%64,%65,%66,%67,%68,%69,%70,%71,%72,%73,%74,%75,%76,%77,%78,%79,%80,%81,%82,%83,%84,%85,%86,%87,%88,%89,%90,%91,%92,%93,%94,%95}, {%96,%97,%98,%99}, %100, p, 1, 1, 1;}\n"
   : "+f"(d[0]),"+f"(d[1]),"+f"(d[2]),"+f"(d[3]),"+f"(d[4]),"+f"(d[5]),"+f"(d[6]),"+f"(d[7]),"+f"(d[8]),"+f"(d[9]),"+f"(d[10]),"+f"(d[11]),"+f"(d[12]),"+f"(d[13]),"+f"(d[14]),"+f"(d[15]),"+f"(d[16]),"+f"(d[17]),"+f"(d[18]),"+f"(d[19]),"+f"(d[20]),"+f"(d[21]),"+f"(d[22]),"+f"(d[23]),"+f"(d[24]),"+f"(d[25]),"+f"(d[26]),"+f"(d[27]),"+f"(d[28]),"+f"(d[29]),"+f"(d[30]),"+f"(d[31]),"+f"(d[32]),"+f"(d[33]),"+f"(d[34]),"+f"(d[35]),"+f"(d[36]),"+f"(d[37]),"+f"(d[38]),"+f"(d[39]),"+f"(d[40]),"+f"(d[41]),"+f"(d[42]),"+f"(d[43]),"+f"(d[44]),"+f"(d[45]),"+f"(d[46]),"+f"(d[47]),"+f"(d[48]),"+f"(d[49]),"+f"(d[50]),"+f"(d[51]),"+f"(d[52]),"+f"(d[53]),"+f"(d[54]),"+f"(d[55]),"+f"(d[56]),"+f"(d[57]),"+f"(d[58]),"+f"(d[59]),"+f"(d[60]),"+f"(d[61]),"+f"(d[62]),"+f"(d[63]),"+f"(d[64]),"+f"(d[65]),"+f"(d[66]),"+f"(d[67]),"+f"(d[68]),"+f"(d[69]),"+f"(d[70]),"+f"(d[71]),"+f"(d[72]),"+f"(d[73]),"+f"(d[74]),"+f"(d[75]),"+f"(d[76]),"+f"(d[77]),"+f"(d[78]),"+f"(d[79]),"+f"(d[80]),"+f"(d[81]),"+f"(d[82]),"+f"(d[83]),"+f"(d[84]),"+f"(d[85]),"+f"(d[86]),"+f"(d[87]),"+f"(d[88]),"+f"(d[89]),"+f"(d[90]),"+f"(d[91]),"+f"(d[92]),"+f"(d[93]),"+f"(d[94]),"+f"(d[95]) : "r"(a.x), "r"(a.y), "r"(a.z), "r"(a.w), "l"(db), "r"(sc));
}
template<int N> __device__ __forceinline__ void wgmma_rs(float* d, const uint32_t* a, uint64_t db, int sc);
template<> __device__ __forceinline__ void wgmma_rs<128>(float* d, const uint32_t* a, uint64_t db, int sc) {
  asm volatile("{.reg .pred p; setp.ne.b32 p, %69, 0;\n"
   "wgmma.mma_async.sync.aligned.m64n128k16.f32.bf16.bf16 {%0,%1,%2,%3,%4,%5,%6,%7,%8,%9,%10,%11,%12,%13,%14,%15,%16,%17,%18,%19,%20,%21,%22,%23,%24,%25,%26,%27,%28,%29,%30,%31,%32,%33,%34,%35,%36,%37,%38,%39,%40,%41,%42,%43,%44,%45,%46,%47,%48,%49,%50,%51,%52,%53,%54,%55,%56,%57,%58,%59,%60,%61,%62,%63}, {%64,%65,%66,%67}, %68, p, 1, 1, 0;}\n"
   : "+f"(d[0]),"+f"(d[1]),"+f"(d[2]),"+f"(d[3]),"+f"(d[4]),"+f"(d[5]),"+f"(d[6]),"+f"(d[7]),"+f"(d[8]),"+f"(d[9]),"+f"(d[10]),"+f"(d[11]),"+f"(d[12]),"+f"(d[13]),"+f"(d[14]),"+f"(d[15]),"+f"(d[16]),"+f"(d[17]),"+f"(d[18]),"+f"(d[19]),"+f"(d[20]),"+f"(d[21]),"+f"(d[22]),"+f"(d[23]),"+f"(d[24]),"+f"(d[25]),"+f"(d[26]),"+f"(d[27]),"+f"(d[28]),"+f"(d[29]),"+f"(d[30]),"+f"(d[31]),"+f"(d[32]),"+f"(d[33]),"+f"(d[34]),"+f"(d[35]),"+f"(d[36]),"+f"(d[37]),"+f"(d[38]),"+f"(d[39]),"+f"(d[40]),"+f"(d[41]),"+f"(d[42]),"+f"(d[43]),"+f"(d[44]),"+f"(d[45]),"+f"(d[46]),"+f"(d[47]),"+f"(d[48]),"+f"(d[49]),"+f"(d[50]),"+f"(d[51]),"+f"(d[52]),"+f"(d[53]),"+f"(d[54]),"+f"(d[55]),"+f"(d[56]),"+f"(d[57]),"+f"(d[58]),"+f"(d[59]),"+f"(d[60]),"+f"(d[61]),"+f"(d[62]),"+f"(d[63]) : "r"(a[0]), "r"(a[1]), "r"(a[2]), "r"(a[3]), "l"(db), "r"(sc));
}
template<> __device__ __forceinline__ void wgmma_rs<96>(float* d, const uint32_t* a, uint64_t db, int sc) {
  asm volatile("{.reg .pred p; setp.ne.b32 p, %53, 0;\n"
   "wgmma.mma_async.sync.aligned.m64n96k16.f32.bf16.bf16 {%0,%1,%2,%3,%4,%5,%6,%7,%8,%9,%10,%11,%12,%13,%14,%15,%16,%17,%18,%19,%20,%21,%22,%23,%24,%25,%26,%27,%28,%29,%30,%31,%32,%33,%34,%35,%36,%37,%38,%39,%40,%41,%42,%43,%44,%45,%46,%47}, {%48,%49,%50,%51}, %52, p, 1, 1, 0;}\n"
   : "+f"(d[0]),"+f"(d[1]),"+f"(d[2]),"+f"(d[3]),"+f"(d[4]),"+f"(d[5]),"+f"(d[6]),"+f"(d[7]),"+f"(d[8]),"+f"(d[9]),"+f"(d[10]),"+f"(d[11]),"+f"(d[12]),"+f"(d[13]),"+f"(d[14]),"+f"(d[15]),"+f"(d[16]),"+f"(d[17]),"+f"(d[18]),"+f"(d[19]),"+f"(d[20]),"+f"(d[21]),"+f"(d[22]),"+f"(d[23]),"+f"(d[24]),"+f"(d[25]),"+f"(d[26]),"+f"(d[27]),"+f"(d[28]),"+f"(d[29]),"+f"(d[30]),"+f"(d[31]),"+f"(d[32]),"+f"(d[33]),"+f"(d[34]),"+f"(d[35]),"+f"(d[36]),"+f"(d[37]),"+f"(d[38]),"+f"(d[39]),"+f"(d[40]),"+f"(d[41]),"+f"(d[42]),"+f"(d[43]),"+f"(d[44]),"+f"(d[45]),"+f"(d[46]),"+f"(d[47]) : "r"(a[0]), "r"(a[1]), "r"(a[2]), "r"(a[3]), "l"(db), "r"(sc));
}
template<> __device__ __forceinline__ void wgmma_rs<64>(float* d, const uint32_t* a, uint64_t db, int sc) {
  asm volatile("{.reg .pred p; setp.ne.b32 p, %37, 0;\n"
   "wgmma.mma_async.sync.aligned.m64n64k16.f32.bf16.bf16 {%0,%1,%2,%3,%4,%5,%6,%7,%8,%9,%10,%11,%12,%13,%14,%15,%16,%17,%18,%19,%20,%21,%22,%23,%24,%25,%26,%27,%28,%29,%30,%31}, {%32,%33,%34,%35}, %36, p, 1, 1, 0;}\n"
   : "+f"(d[0]),"+f"(d[1]),"+f"(d[2]),"+f"(d[3]),"+f"(d[4]),"+f"(d[5]),"+f"(d[6]),"+f"(d[7]),"+f"(d[8]),"+f"(d[9]),"+f"(d[10]),"+f"(d[11]),"+f"(d[12]),"+f"(d[13]),"+f"(d[14]),"+f"(d[15]),"+f"(d[16]),"+f"(d[17]),"+f"(d[18]),"+f"(d[19]),"+f"(d[20]),"+f"(d[21]),"+f"(d[22]),"+f"(d[23]),"+f"(d[24]),"+f"(d[25]),"+f"(d[26]),"+f"(d[27]),"+f"(d[28]),"+f"(d[29]),"+f"(d[30]),"+f"(d[31]) : "r"(a[0]), "r"(a[1]), "r"(a[2]), "r"(a[3]), "l"(db), "r"(sc));
}
template<> __device__ __forceinline__ void wgmma_rs<32>(float* d, const uint32_t* a, uint64_t db, int sc) {
  asm volatile("{.reg .pred p; setp.ne.b32 p, %21, 0;\n"
   "wgmma.mma_async.sync.aligned.m64n32k16.f32.bf16.bf16 {%0,%1,%2,%3,%4,%5,%6,%7,%8,%9,%10,%11,%12,%13,%14,%15}, {%16,%17,%18,%19}, %20, p, 1, 1, 0;}\n"
   : "+f"(d[0]),"+f"(d[1]),"+f"(d[2]),"+f"(d[3]),"+f"(d[4]),"+f"(d[5]),"+f"(d[6]),"+f"(d[7]),"+f"(d[8]),"+f"(d[9]),"+f"(d[10]),"+f"(d[11]),"+f"(d[12]),"+f"(d[13]),"+f"(d[14]),"+f"(d[15]) : "r"(a[0]), "r"(a[1]), "r"(a[2]), "r"(a[3]), "l"(db), "r"(sc));
}

__device__ __forceinline__ void conv_dupA(uint32_t* A, uint32_t zz) {
#pragma unroll
  for (int s = 0; s < 4; s++) {
    asm volatile("xor.b32 %0, %1, %2;" : "=r"(A[4 * s + 3]) : "r"(A[4 * s]), "r"(zz));
    if (s < 3) asm volatile("xor.b32 %0, %1, %2;" : "=r"(A[4 * s + 6]) : "r"(A[4 * s + 1]), "r"(zz));
  }
}
template <int OFF, int DUP = 1> __device__ __forceinline__ void conv_ldA(uint32_t* A, uint32_t ra, uint32_t zz) {
  A[2] = lds32(ra + OFF);
#pragma unroll
  for (int s = 0; s < 4; s++) { A[4 * s] = lds32(ra + OFF + 32 * s + 16); A[4 * s + 1] = lds32(ra + OFF + 32 * s + 32); }
  if (DUP) conv_dupA(A, zz);
}
template <int N, int H, int ACC = 0> __device__ __forceinline__ void conv_grp(float* T, const uint32_t* A, uint64_t dX) {
  WG_FENCE();
#pragma unroll
  for (int s = 0; s < 4; s++) wgmma_rs<N>(T, A + 4 * s, dX - (4 * H + s), (ACC || H > 0 || s > 0));
  WG_COMMIT();
}
template <int H> __device__ __forceinline__ void conv_grp2(float* T, float* U, const uint32_t* A, uint64_t dX) {
  WG_FENCE();
#pragma unroll
  for (int s = 0; s < 4; s++) {
    wgmma_rs<64>(T, A + 4 * s, dX + 32 - (4 * H + s), (H > 0 || s > 0));
    wgmma_rs<32>(U, A + 4 * s, dX - (4 * H + s), (H > 0 || s > 0));
  }
  WG_COMMIT();
}

__device__ __forceinline__ void red_ld(uint4 (*v)[4], uint32_t pb, uint32_t pitch, int idx) {
  const int a = idx >> 1, half = idx & 1;
  const uint32_t p0 = pb + half * 2048 + ((a ^ (half << 2)) << 4), p2 = p0 + pitch - 256;
#pragma unroll
  for (int n = 0; n < 2; n++)
#pragma unroll
    for (int q = 0; q < 4; q++) { v[n][q] = make_uint4(0, 0, 0, 0); if (n > 0 || a >= 8 * q) v[n][q] = lds128((q < 2 ? p0 : p2) + (q & 1) * 3968 + n * 1024); }
}
__device__ __forceinline__ void red_st(const uint4 (*v)[4], uint32_t zo, int idx, int on) {
#pragma unroll
  for (int m = 0; m < 2; m++)
    asm volatile("{.reg .pred p; setp.ne.b32 p, %5, 0; @p st.shared.v4.u32 [%0], {%1,%2,%3,%4};}" ::"r"(zo + idx * 16 + m * 2048),
                 "r"(badd2(badd2(v[m][0].x, v[m][1].x), badd2(v[m][2].x, v[m][3].x))), "r"(badd2(badd2(v[m][0].y, v[m][1].y), badd2(v[m][2].y, v[m][3].y))),
                 "r"(badd2(badd2(v[m][0].z, v[m][1].z), badd2(v[m][2].z, v[m][3].z))), "r"(badd2(badd2(v[m][0].w, v[m][1].w), badd2(v[m][2].w, v[m][3].w))), "r"(on) : "memory");
}
__device__ __forceinline__ void red_fin(uint32_t bar, int on) {
  asm volatile("fence.proxy.async.shared::cta;" ::: "memory");
  asm volatile("{.reg .pred p; setp.ne.b32 p, %1, 0; @p mbarrier.arrive.shared::cta.b64 _, [%0];}" ::"r"(bar), "r"(on) : "memory");
}

__global__ void __launch_bounds__(384, 1) fused_kernel(const __grid_constant__ Maps maps, const Ptrs P, const uint32_t zz) {
  extern __shared__ __align__(1024) uint8_t smem[];
  constexpr uint32_t sb = 1024;
  const int tid = threadIdx.x;
  const int b = blockIdx.x;
  const uint32_t bars = sb + SM_BAR;

#define BAR(i) (bars + 8u * (i))
  TR(t63);
  const int rt = (b >> 1) & 15, ct = (b & 1) | ((b >> 5) << 1);
  const int rb = b >> 2, cb = b & 3;
  const int b2 = cb * 32 + rb;
  const int ch0 = cb * 160 + rb;

  if ((tid >> 5) == 8) {
    if (elect_one()) {
      mbar_init(BAR(B_FX), 1); mbar_init(BAR(B_FW), 1); mbar_init(BAR(B_FW + 1), 1);
      asm volatile("fence.proxy.async.shared::cta;" ::: "memory");
      mbar_expect_tx(BAR(B_FX), 16384); tma2d(sb + SM_X, &maps.x, BAR(B_FX), 0, rt * 128);
#pragma unroll
      for (int n = 0; n < NPRE; n++) {
        mbar_expect_tx(BAR(B_FW + n), 24576);
        tma3d(sb + SM_W + n * 24576, &maps.wg, BAR(B_FW + n), 0, n * 32, ct * 3); tma3d(sb + SM_W + n * 24576 + 12288, &maps.wu, BAR(B_FW + n), 0, n * 32, ct * 3);
      }
      mbar_init(BAR(B_FX + 1), 1); mbar_init(BAR(B_FX + 2), 1); mbar_init(BAR(B_FW + 2), 1);
      asm volatile("fence.proxy.async.shared::cta;" ::: "memory");
    }
  }
  const int wg = __shfl_sync(0xffffffffu, tid >> 7, 0);

  if (wg == 2) {
    asm volatile("setmaxnreg.dec.sync.aligned.u32 40;");
    bar_sync(0, 384);
    const int warp = __shfl_sync(0xffffffffu, tid >> 5, 0) - 8, lane = tid & 31;
    if (warp == 0) {
      if (elect_one()) {
        TS1(11); TW(9, t9); TW(10, t10);
#pragma unroll
        for (int n = NPRE; n < 20; n++) {
          const int k = n < 14 ? (n >> 1) : n < 17 ? n - 7 : n - 10;
          const bool up = n < 14 ? (n & 1) : (n >= 17);
          if (n == PF_N) { tma3d_prefetch(&maps.wu, 0, 576, ct * 3); tma3d_prefetch(&maps.wu, 0, 608, ct * 3); }
          if (!up && n != 16) {
            const int xs = k % 3;
            if (k >= 3) mbar_wait(BAR(B_EX + xs), ((k / 3) - 1) & 1);
            mbar_expect_tx(BAR(B_FX + xs), 16384);
            tma2d(sb + SM_X + xs * 16384, &maps.x, BAR(B_FX + xs), k * 64, rt * 128);
          }
          const int s = n % 5;
          if (n >= 5) mbar_wait(BAR(B_EW + s), ((n / 5) - 1) & 1);
          mbar_expect_tx(BAR(B_FW + s), 24576);
          tma3d(sb + SM_W + s * 24576, n >= 17 ? &maps.wu : &maps.wg, BAR(B_FW + s), 0, n < 14 ? n * 32 : k * 64, ct * 3);
          tma3d(sb + SM_W + s * 24576 + 12288, n < 14 || n >= 17 ? &maps.wu : &maps.wg, BAR(B_FW + s), 0, n < 14 ? n * 32 : k * 64 + 32, ct * 3);
          if (n == X9_N) {
            mbar_wait(BAR(B_GF), 0);
            TS1(33);
            mbar_expect_tx(BAR(B_F9), 16384);
            tma2d(sb + SM_GAP, &maps.x, BAR(B_F9), 576, rt * 128);
          }
          if (n == KV0 || n == KV1 || n == KV2 || n == KV3 || n == KV4) {
            const int r = n == KV0 ? 0 : n == KV1 ? 1 : n == KV2 ? 2 : n == KV3 ? 3 : 4;
            mbar_expect_tx(BAR(B_KV + r), 8576);
            tma3d(sb + SM_D + r * 8576, &maps.k, BAR(B_KV + r), 0, (b >> 1) * 32 - 3, (b & 1) * 10 + 2 * r);
            tma3d(sb + SM_D + r * 8576 + 4480, &maps.v, BAR(B_KV + r), 0, (b >> 1) * 32, (b & 1) * 10 + 2 * r);
          }
          if (n >= SK_N && n < SK_N + 5) l2_prefetch(P.ssm_k + (size_t)(ch0 + 32 * (n - SK_N)) * 2048, 4096);
          if (n == WD_N) {
            mbar_expect_tx(BAR(B_WD), b < 120 ? 16384 : 0);
            if (b < 120) tma3d(sb + SM_GAP, &maps.wd, BAR(B_WD), 0, (b / 5) * 64, (b % 5) * 4);
          }
        }
        TS1(32);
        mbar_wait(BAR(B_PRE), 0);
        const uint32_t target = lds32v(sb + SM_BAR + 576);
        mbar_wait(BAR(B_EW + 0), 1);
        flag_wait(&g_cnt[0], target);
        mbar_expect_tx(BAR(B_XI), 5 * XCH);
        tma3d(sb + SM_W, &maps.xl, BAR(B_XI), 0, -2, b2 * 10);
        TS1(1);
        const uint8_t* wsrc = g_wd + cb * 20480;
        mbar_wait(BAR(B_G1), 0);
        for (int s = 0; s < 4; s++) {
          mbar_expect_tx(BAR(B_F2 + s), 28672);
          bulk_g2s(sb + SM_R2 + s * 28672 + 8192, wsrc + s * 81920, 20480, BAR(B_F2 + s));
        }
        TS1(2);
        flag_wait(&g_cnt[(1 + rb) * 32], target);
        TS1(3);
        const uint8_t* hsrc = g_h + (size_t)rb * 24 * 8192;
        for (int s = 0; s < 4; s++) {
          if (!(s & 1)) mbar_wait(BAR(B_ZR + (s >> 1)), 0);
          bulk_g2s(sb + SM_R2 + s * 28672, hsrc + s * 8192, 8192, BAR(B_F2 + s));
        }
        mbar_expect_tx(BAR(B_Q), 256);
        bulk_g2s(sb + SM_GT, g_gate + rb * 64, 256, BAR(B_Q));
        tmap_prefetch(&maps.z);
        for (int c = 4, s = 0, ph = 0; c < 24; c++) {
          if (c == 8) mbar_wait(BAR(B_ZR + 2), 0); else mbar_wait(BAR(B_E2 + s), s == 4 ? ph ^ 1 : ph);
          mbar_expect_tx(BAR(B_F2 + s), 28672);
          bulk_g2s(s == 4 ? sb + SM_W : sb + SM_R2 + s * 28672, hsrc + c * 8192, 8192, BAR(B_F2 + s));
          bulk_g2s(s == 4 ? sb + SM_W + 24576 : sb + SM_R2 + s * 28672 + 8192, wsrc + c * 81920, 20480, BAR(B_F2 + s));
          if (++s == 5) { s = 0; ph ^= 1; }
        }
        TS1(4);
      }
    } else {
      const int hw = warp - 1;
      if (hw == 2) {
        if (smem_u32(smem) != sb) asm volatile("trap;");
        const int c8 = lane & 7, r4 = lane >> 3;
        float acc[4] = {0.f, 0.f, 0.f, 0.f};
        uint4 gw = __ldg((const uint4*)(P.gate_w + c8 * 8));
        gw.x |= __ldg((const uint32_t*)(P.gate_w + 128 + lane * 16)) & zz;
        uint32_t xs = 0, xph = 0;
        const __nv_bfloat16* pw = (lane & 1 ? P.wu : P.wg) + (rt * 4 + (lane >> 3)) * 1536 + ct * 192 + ((lane >> 1) & 3) * 64;
        const __nv_bfloat16* px = P.x + (rt * 128 + ct * 16 + (lane & 15)) * 640;
        const bool pfw = (lane & 6) != 6;
#define PFK(kk) { if (pfw) asm volatile("prefetch.global.L2 [%0];" ::"l"(pw + (kk) * 98304)); if (lane < 16) asm volatile("prefetch.global.L2 [%0];" ::"l"(px + (kk) * 64)); }
        for (int k = PF0; k < PD; k++) PFK(k)
#pragma unroll 1
        for (int k = 0; k < 10; k++) {
          const uint4 gn = __ldg((const uint4*)(P.gate_w + (k < 9 ? k + 1 : 0) * 64 + c8 * 8));
          if (k == 9) { xs = 3; mbar_wait(BAR(B_F9), 0); } else mbar_wait(BAR(B_FX + xs), xph);
          if (k + PD < 10) PFK(k + PD)
#pragma unroll
          for (int i = 0; i < 4; i++) {
            const int row = (i >> 1) * 64 + ct * 8 + (i & 1) * 4 + r4;
            const uint4 v = lds128(sb + SM_X + xs * 16384 + row * 128 + ((c8 ^ (row & 7)) << 4));
            const uint32_t p[4] = {bmul2(v.x, gw.x), bmul2(v.y, gw.y), bmul2(v.z, gw.z), bmul2(v.w, gw.w)};
#pragma unroll
            for (int e = 0; e < 4; e++) acc[i] += __uint_as_float(p[e] << 16) + __uint_as_float(p[e] & 0xffff0000u);
          }
          __syncwarp();
          if (lane == 0 && k < 6) mbar_arrive(BAR(B_EX + xs));
          if (lane == 0 && k == WK) {
            mbar_wait(BAR(B_WD), 0);
            if (b < 120) bulk_s2g(g_wd + (size_t)b * 16384, sb + SM_GAP, 16384);
            asm volatile("cp.async.bulk.commit_group;" ::: "memory");
          }
          if (lane == 0 && k == WK + 1) {
            asm volatile("cp.async.bulk.wait_group 0;" ::: "memory");
            mbar_arrive(BAR(B_GF));
          }
          __syncwarp();
          if (++xs == 3) { xs = 0; xph ^= 1; }
          gw = gn;
        }
#pragma unroll
        for (int i = 0; i < 4; i++)
#pragma unroll
          for (int o = 1; o < 8; o <<= 1) acc[i] += __shfl_xor_sync(0xffffffffu, acc[i], o);
        if (c8 < 4) {
          const float sv = c8 == 0 ? acc[0] : c8 == 1 ? acc[1] : c8 == 2 ? acc[2] : acc[3];
          const float l = __bfloat162float(__float2bfloat16_rn(sv));
          const float gv = __bfloat162float(__float2bfloat16_rn(1.0f / (1.0f + __expf(-l))));
          asm volatile("st.shared.f32 [%0], %1;" ::"r"(sb + SM_GO + c8 * 16 + r4 * 4), "f"(gv) : "memory");
          asm volatile("fence.proxy.async.shared::cta;" ::: "memory");
        }
        __syncwarp();
        if (lane == 0) { mbar_arrive(BAR(B_G1)); mbar_arrive(BAR(B_HS + 0)); mbar_arrive(BAR(B_HS + 1)); TS1(7); }
      } else {
        const int ht = tid - 288;
        const int rc = b >> 1, chb = (b & 1) * 320;
        const int cl = hw * 32 + (lane >> 1) * 2;
        const __nv_bfloat16* skp = P.shift_k + (chb + cl) * 4;
        uint4 sk = __ldg((const uint4*)skp);
        if (ht < 20) asm volatile("prefetch.global.L2 [%0];" ::"l"(P.shift_k + chb * 4 + ht * 64));
        uint32_t ka = sb + SM_D + hw * 2240 + (lane >> 1) * 4 + (lane & 1) * 1024;
        const uint32_t vo = 4480 - hw * 192, so = 4480 - hw * 192 + (lane >> 1) * 28 - (lane & 1) * 1008;
#pragma unroll 1
        for (int pg = 0; pg < 5; pg++) {
          const uint32_t w0 = __byte_perm(sk.x, sk.z, 0x5410), w1 = __byte_perm(sk.x, sk.z, 0x7632);
          const uint32_t w2 = __byte_perm(sk.y, sk.w, 0x5410), w3 = __byte_perm(sk.y, sk.w, 0x7632);
          sk = __ldg((const uint4*)(skp + (pg < 4 ? pg + 1 : 0) * 256));
          mbar_wait(BAR(B_KV + pg), 0);
          if (ht == 0) TS1(21 + pg);
          uint32_t kk[19], o[8];
#pragma unroll
          for (int i = 0; i < 11; i++) kk[i] = lds32(ka + i * 64);
#pragma unroll
          for (int h = 0; h < 2; h++) {
#pragma unroll
            for (int i = 0; i < 8; i++) o[i] = lds32(ka + vo + (8 * h + i) * 64);
#pragma unroll
            for (int i = 0; i < 8; i++) o[i] = bmul2(bfma2(kk[8 * h + i + 3], w0, bfma2(kk[8 * h + i + 2], w1, bfma2(kk[8 * h + i + 1], w2, bmul2(kk[8 * h + i], w3)))), o[i]);
            if (h == 0) {
#pragma unroll
              for (int i = 11; i < 19; i++) kk[i] = lds32(ka + i * 64);
            }
            __syncwarp();
            sts128(ka + so + h * 512, __byte_perm(o[1], o[0], 0x5410), __byte_perm(o[3], o[2], 0x5410), __byte_perm(o[5], o[4], 0x5410), __byte_perm(o[7], o[6], 0x5410));
            sts128(ka + so + h * 512 + 1024, __byte_perm(o[1], o[0], 0x7632), __byte_perm(o[3], o[2], 0x7632), __byte_perm(o[5], o[4], 0x7632), __byte_perm(o[7], o[6], 0x7632));
          }
          asm volatile("fence.proxy.async.shared::cta;" ::: "memory");
          __syncwarp();
          if (lane == 0) {
            const int blk = (b & 1) * 10 + 2 * pg + hw;
            asm volatile("cp.async.bulk.tensor.5d.global.shared::cta.bulk_group [%0, {%2,%3,%3,%3,%4}], [%1];" ::"l"(&maps.xs), "r"(ka + vo), "r"(rc * 16), "r"(0), "r"((blk / 5) * 160 + blk % 5) : "memory");
          }
          ka += 8576;
        }
        if (lane == 0) {
          asm volatile("cp.async.bulk.commit_group;" ::: "memory");
          asm volatile("cp.async.bulk.wait_group.read 0;" ::: "memory");
        }
        bar_sync(3, 64);
        if (ht == 0) {
          TS1(12);
          mbar_expect_tx(BAR(B_HR), 20480);
          for (int c = 0; c < 5; c++) bulk_g2s(sb + SM_D + 128 + c * TP + 4128, P.ssm_k + (size_t)(ch0 + 32 * c) * 2048, 4096, BAR(B_HR));
        }
        uint32_t old = 0;
        if (lane == 0) {
          asm volatile("cp.async.bulk.wait_group 0;" ::: "memory");
          mbar_arrive(BAR(B_KD));
          if (hw) {
            TS1(6);
            mbar_wait(BAR(B_KD), 0);
            mbar_wait(BAR(B_GF), 0);
            TS1(20);
            asm volatile("atom.relaxed.gpu.global.add.u32 %0, [%1], 1;" : "=r"(old) : "l"(&g_cnt[0]) : "memory");
          }
        }
        if (lane < 20) sts128(sb + SM_D + 96 + (lane >> 2) * TP + ((lane >> 1) & 1) * 4128 + (lane & 1) * 16, 0, 0, 0, 0);
        uint32_t dv = 0;
        if (ht < 5) dv = __ldg((const unsigned short*)(P.ssm_D + ch0 + 32 * ht));
        mbar_wait(BAR(B_HR), 0);
        if (ht < 5) {
          const uint32_t a0 = sb + SM_D + 128 + 4128 + ht * TP;
          asm volatile("st.shared.u32 [%0], %1;" ::"r"(a0), "r"(badd2(lds32(a0), dv)) : "memory");
        }
        __syncwarp();
        if (ht == 32) TS1(13);
#pragma unroll 1
        for (int c = 0; c < 5; c++) {
          const uint32_t d = sb + SM_D + 128 + c * TP + hw * 2048 + lane * 16;
          uint4 v[4]; uint32_t pv[4];
#pragma unroll
          for (int i = 0; i < 4; i++) { v[i] = lds128(d + 4128 + i * 512); pv[i] = lds32(d + 4124 + i * 512); }
#pragma unroll
          for (int i = 0; i < 4; i++)
            sts128(d + i * 512, __byte_perm(pv[i], v[i].x, 0x5432), __byte_perm(v[i].x, v[i].y, 0x5432), __byte_perm(v[i].y, v[i].z, 0x5432), __byte_perm(v[i].z, v[i].w, 0x5432));
          if (c == 1 && ht == 32) { asm volatile("st.shared.u32 [%0], %1;" ::"r"(sb + SM_BAR + 576), "r"((old & ~127u) + 128u) : "memory"); mbar_arrive(BAR(B_PRE)); TS1(8); }
        }
        __syncwarp();
        if (lane == 0) {
          mbar_arrive(BAR(B_HC));
          if (hw) TS1(14);
          mbar_wait(BAR(B_HS + hw), 0);
          TS1(5 + hw * 10);
          bulk_s2g(g_h + ((size_t)(rt * 2 + hw) * 24 + ct * 3) * 8192, sb + SM_W + (1 + hw) * 24576, 24576);
          bulk_s2g(g_gate + rt * 128 + hw * 64 + ct * 8, sb + SM_GO + hw * 32, 32);
          asm volatile("cp.async.bulk.commit_group;" ::: "memory");
          asm volatile("cp.async.bulk.wait_group.read 0;" ::: "memory");
          mbar_arrive(BAR(B_HF + hw));
          asm volatile("cp.async.bulk.wait_group 0;" ::: "memory");
          flag_add_relaxed(&g_cnt[(1 + rt * 2 + hw) * 32], 16);
          TS1(26 + hw);
        }
        __syncwarp();
      }
      if (tid == 320) {
#pragma unroll 1
        for (int c = 0; c < 4; c++) {
          mbar_wait(BAR(B_ZR + c), 0);
          TS1(16 + c);
          bulk_s2g(g_z + (size_t)(ch0 + 32 * c) * 4096, sb + SM_D + 128 + c * TP, 4096);
          asm volatile("cp.async.bulk.commit_group;" ::: "memory");
          if (c == QC) {
            asm volatile("cp.async.bulk.wait_group.read %0;" :: "n"(QC - 1) : "memory");
            mbar_wait(BAR(B_HF), 0);
            mbar_expect_tx(BAR(B_Q), 36864);
            for (int i = 0; i < 5; i++) tma3d(i < 4 ? sb + SM_D + i * 4096 : sb + SM_W + 45056, &maps.q, BAR(B_Q), 0, rb * 64, cb * 5 + i);
          }
        }
      }
      if (tid == 288) {
        mbar_wait(BAR(B_ZR + 4), 0);
        bulk_s2g(g_z + (size_t)(ch0 + 128) * 4096, sb + SM_D + 128 + 4 * TP, 4096);
        asm volatile("cp.async.bulk.commit_group;" ::: "memory");
        mbar_expect_tx(BAR(B_Q2), 4096);
      }
      if (tid == 288 || tid == 320) {
        uint32_t* fl = &g_cnt[(tid == 288 ? 37 : 33) * 32 + cb * 32];
        asm volatile("cp.async.bulk.wait_group 0;" ::: "memory");
        flag_add_relaxed(fl, 4);
        TS1(tid == 288 ? 30 : 28);
        flag_wait(fl, lds32v(sb + SM_BAR + 576));
        TS1(tid == 288 ? 31 : 29);
        for (int i = tid == 288 ? 4 : 0; i < (tid == 288 ? 5 : 4); i++) tma2d(sb + SM_D + 16384 + i * 4096, &maps.z, BAR(tid == 288 ? B_Q2 : B_Q), rb * 64, cb * 160 + 32 * i);
      }
    }
  } else {
    {
      uint32_t tq;
      asm volatile("mov.u32 %0, %%tid.x;" : "=r"(tq));
      const int wi = __shfl_sync(0xffffffffu, tq >> 5, 0);
      if (elect_one()) {
#pragma unroll 1
        for (int gi = wi + 1; gi < 12; gi += 8) {
          const uint32_t cnt = gi < 5 ? 1 : (uint32_t)(0x80808102040908ull >> (8 * (gi - 5))) & 0xff;
#pragma unroll
          for (int j = 0; j < 6; j++) mbar_init(BAR(gi * 6 + j), cnt);
        }
        asm volatile("fence.proxy.async.shared::cta;" ::: "memory");
      }
      __syncwarp();
    }
    bar_sync(0, 384);
    asm volatile("setmaxnreg.inc.sync.aligned.u32 232;");
    const int t128 = tid & 127, w = __shfl_sync(0xffffffffu, t128 >> 5, 0), lane = tid & 31;
    const uint32_t ra0 = sb + SM_D + 128 + (((lane >> 2) & 1) ? 4128 + 2 * (128 * w + (lane >> 2) - 2 * (lane & 3) - 9) : 2 * (128 * w + (lane >> 2) - 2 * (lane & 3) - 8));
    uint32_t A0[16], A1[16], A2[16];
    {
      float ag[96], au[96];
      const uint64_t dA0 = mkdesc(sb + SM_X + wg * 8192, 16, 1024, 1);
      const uint64_t dB0 = mkdesc(sb + SM_W, 4096, 1024, 1);
      const uint32_t xa = sb + SM_X + wg * 8192 + (16 * w + (lane & 15)) * 128 + (((lane >> 4) ^ (lane & 7)) << 4);
      uint4 A[2];
      TS(18);
      mbar_wait(BAR(B_FX + 0), 0);
      TS(19);
      A[0] = ldsm4(xa);
#pragma unroll
      for (int st = 0; st < 28; st++) {
        const int k = st >> 2, kk = st & 3, n = st >> 1, xs = k % 3;
        if (!(st & 1)) mbar_wait(BAR(B_FW + n % 5), (n / 5) & 1);
        if (LSTEP && st > 0 && st % (LSTEP + !LSTEP) == 0) bar_sync(7, 256);
        if (kk == 0) TS(20 + k);
        WG_FENCE();
        wgmma_rs_tb_n192(ag, A[st & 1], dB0 + (n % 5) * 1536 + (st & 1) * 128, st > 0);
        wgmma_rs_tb_n192(au, A[st & 1], dB0 + (n % 5) * 1536 + 768 + (st & 1) * 128, st > 0);
        WG_COMMIT();
        if (kk == 3 && k < 6 && lane == 0) mbar_arrive(BAR(B_EX + xs));
        WG_WAIT(1);
        if (!(st & 1) && st > 0 && lane == 0) mbar_arrive(BAR(B_EW + (n - 1) % 5));
        if (kk < 3) A[(kk + 1) & 1] = ldsm4((xa ^ ((kk + 1) << 5)) + xs * 16384);
        else if (k < 6) { mbar_wait(BAR(B_FX + (k + 1) % 3), ((k + 1) / 3) & 1); A[0] = ldsm4(xa + ((k + 1) % 3) * 16384); }
      }
      TS(1);
#define G1_UNITS(acc, xsl, wsl) { WG_FENCE(); _Pragma("unroll") for (int kk = 0; kk < 4; kk++) { wgmma_ss_tb_n192(acc, dA0 + (xsl) * 1024 + kk * 2, dB0 + (wsl) * 1536 + (kk >> 1) * 768 + (kk & 1) * 128, 1); if (kk == 3 - HOFF) WG_COMMIT(); } WG_COMMIT(); }
#define G1_UNIT(acc, xsl, wsl) { WG_FENCE(); _Pragma("unroll") for (int kk = 0; kk < 4; kk++) wgmma_ss_tb_n192(acc, dA0 + (xsl) * 1024 + kk * 2, dB0 + (wsl) * 1536 + (kk >> 1) * 768 + (kk & 1) * 128, 1); WG_COMMIT(); }
      mbar_wait(BAR(B_FX + 1), 0);
      mbar_wait(BAR(B_FW + 4), 0);
      if (wg) {
        WG_WAIT(0);
        if (lane == 0) mbar_arrive(BAR(B_EW + 3));
        bar_sync(4, 256);
      }
      TS(8);
      G1_UNIT(ag, 1, 4);
      WG_WAIT(1);
      if (lane == 0 && !wg) mbar_arrive(BAR(B_EW + 3));
      mbar_wait(BAR(B_FX + 2), 0);
      mbar_wait(BAR(B_FW + 0), 1);
      TS(6);
      G1_UNIT(ag, 2, 0);
      WG_WAIT(1);
      if (lane == 0) mbar_arrive(BAR(B_EW + 4));
      TS(9);
      mbar_wait(BAR(B_F9), 0);
      mbar_wait(BAR(B_FW + 1), 1);
      TS(16);
      G1_UNITS(ag, 3, 1);
      WG_WAIT(1);
      bar_arrive(4 + wg, 256);
      TS(14);
      if (lane == 0) mbar_arrive(BAR(B_EW + 0));
      WG_WAIT(0);
      if (lane == 0) mbar_arrive(BAR(B_EW + 1));
      TS(2);
      uint32_t sg[48], dep;
#define SIG(lo, hi) dep = sig_range<lo, hi>(ag, sg, zz);
      SIG(0, SG0)
      TS(15);
      mbar_wait(BAR(B_FW + 2) + dep, 1);
      mbar_wait(BAR(B_FW + 3), 1);
      bar_sync(5 + wg, 256);
      TS(17);
      WG_FENCE();
#define U1(xsl, wsl, kk) wgmma_ss_tb_n192(au, dA0 + (xsl) * 1024 + kk * 2, dB0 + ((wsl) * 1536 + (kk >> 1) * 768 + (kk & 1) * 128 + dep), 1);
#define SGC(n) ((SG0 + (n) * SG1) < 48 ? (SG0 + (n) * SG1) : 48)
      U1(1, 2, 0) U1(1, 2, 1) U1(1, 2, 2) SIG(SGC(0), SGC(1))
      U1(1, 2, 3) WG_COMMIT(); SIG(SGC(1), SGC(2))
      U1(2, 3, 0) SIG(SGC(2), SGC(3))
      U1(2, 3, 1) SIG(SGC(3), SGC(4))
      U1(2, 3, 2) SIG(SGC(4), SGC(5))
      U1(2, 3, 3) WG_COMMIT(); SIG(SGC(5), 48)
      WG_WAIT(1);
      if (lane == 0) mbar_arrive(BAR(B_EW + 2));
      TS(10);
      mbar_wait(BAR(B_FW + 4) + dep, 1);
      TS(12);
      G1_UNITS(au, 3, 4);
      mbar_wait(BAR(B_HC), 0);
      conv_ldA<0, 0>(A0, ra0 + wg * TP, zz); conv_ldA<128, 0>(A1, ra0 + wg * TP, zz);
      WG_WAIT(1);
      if (!wg) bar_arrive(6, 256);
      TS(3);
      mbar_wait(BAR(B_EW + 1 + wg), 1);
      WG_WAIT(0);
      if (lane == 0) mbar_arrive(BAR(B_G1));
      TS(4);
      const uint32_t hb = sb + SM_W + (1 + wg) * 24576 + (16 * w + (lane & 15)) * 128;
#pragma unroll
      for (int j = 0; j < 24; j += 2) {
        uint32_t p[4];
#pragma unroll
        for (int e = 0; e < 4; e++) p[e] = bmul2(sg[2 * j + e], pack_bf16(au[4 * j + 2 * e], au[4 * j + 2 * e + 1]));
        const int cc = (j & 7) + (lane >> 4);
        stsm4(hb + (j >> 3) * 8192 + ((cc ^ (lane & 7)) << 4), p[0], p[1], p[2], p[3]);
      }
      asm volatile("fence.proxy.async.shared::cta;" ::: "memory");
      mbar_arrive(BAR(B_HS + wg));
      TS(5);
    }
    {
      uint32_t pb = sb + SM_R2 + wg * 57344, pitch = 28672;
      const uint32_t po = (w & 1) * 4096 + (lane & 8) * 256 + (8 * (lane >> 4) + ((lane & 7) ^ ((lane & 8) >> 1))) * 16;
      mbar_wait(BAR(B_XI), 0);
      const int c_end = 4 + wg;
      conv_dupA(A0, zz); conv_dupA(A1, zz);
#pragma unroll 1
      for (int c = wg, cn, cp = 0; c < c_end; cp = c, c = cn) {
        cn = c == 3 ? 4 : c + 2;
        const uint32_t ra = ra0 + c * TP;
        const uint64_t dX = mkdesc(sb + SM_W + c * XCH + 256, XP, 128, 0);
        float T0[64], T1[16], T2[32], T3[16];
        TS(27 + (c >> 1));
        uint4 v[2][4];
        WG_FENCE();
#pragma unroll
        for (int s = 0; s < 8; s++) {
          wgmma_rs<128>(T0, (s < 4 ? A0 : A1 - 16) + 4 * s, dX - s, s > 0);
          if (s == 3 || s == 7) WG_COMMIT();
          if (s == RP0) { bar_sync(1 + wg, 128); red_ld(v, pb, pitch, t128); }
          if (s == RP1) red_st(v, sb + SM_D + 128 + cp * TP, t128, c >= 2);
          if (s == RP2) { red_fin(BAR(B_ZR + cp), c >= 2); TS(33 + (cp >> 1)); }
        }
        if (c >= 2) { pb = sb + SM_W + (1 + wg) * 24576; pitch = 8192; }
        conv_ldA<3072>(A2, ra, zz);
        conv_grp<32, 0>(T3, A2, dX);
        WG_WAIT(2); conv_ldA<3072 + 128>(A0, ra, zz);
        conv_grp<32, 1>(T3, A0, dX);
        WG_WAIT(2); conv_ldA<1024>(A1, ra, zz);
        conv_grp2<0>(T2, T1, A1, dX);
        WG_WAIT(2); conv_ldA<1024 + 128>(A2, ra, zz);
        conv_grp2<1>(T2, T1, A2, dX);
        WG_WAIT(2); conv_ldA<2048>(A0, ra, zz);
        conv_grp<64, 0, 1>(T2, A0, dX);
#pragma unroll
        for (int i = 0; i < 16; i++) fadd_v(T0[48 + i], T3[i]);
        WG_WAIT(2); conv_ldA<2048 + 128>(A1, ra, zz);
        conv_grp<64, 1>(T2, A1, dX);
        WG_WAIT(2);
#pragma unroll
        for (int i = 0; i < 16; i++) fadd_v(T0[16 + i], T1[i]);
        const uint32_t rn = cn < c_end ? ra0 + cn * TP : ra;
        WG_WAIT(1); conv_ldA<0>(A0, rn, zz);
        mbar_wait(BAR(c < 2 ? B_G1 : c == 4 ? B_ZR + 3 : B_HF + wg), 0);
        const uint32_t pa = pb + po + (w >> 1) * pitch;
#pragma unroll
        for (int j = 0; j < 8; j += 2)
          stsm4t(pa + j * 128, pack_bf16(T0[4 * j], T0[4 * j + 1]), pack_bf16(T0[4 * j + 2], T0[4 * j + 3]), pack_bf16(T0[4 * j + 4], T0[4 * j + 5]), pack_bf16(T0[4 * j + 6], T0[4 * j + 7]));
        WG_WAIT(0); conv_ldA<128>(A1, rn, zz);
        TS(30 + (c >> 1));
#pragma unroll
        for (int i = 0; i < 32; i++) T0[32 + i] += T2[i];
#pragma unroll
        for (int j = 8; j < 16; j += 2)
          stsm4t(pa + j * 128, pack_bf16(T0[4 * j], T0[4 * j + 1]), pack_bf16(T0[4 * j + 2], T0[4 * j + 3]), pack_bf16(T0[4 * j + 4], T0[4 * j + 5]), pack_bf16(T0[4 * j + 6], T0[4 * j + 7]));
      }
      TS(7);
    }
    const int g = lane >> 2;
    const int frow = 16 * w + (lane & 7) + 8 * ((lane >> 3) & 1);
    const uint32_t fo = frow * 64 + (((lane >> 4) ^ ((frow >> 1) & 3)) << 4);
    const uint32_t og = sb + SM_W + 2 * 24576 + frow * 336 + ((lane >> 4) << 4);
    if (wg == 0) {
      float acc[80];
      const uint64_t dA0 = mkdesc(sb + SM_R2, 16, 1024, 1), dA4 = mkdesc(sb + SM_W, 16, 1024, 1);
      const uint64_t dB0 = mkdesc(sb + SM_R2 + 8192, 4096, 512, 2), dB4 = mkdesc(sb + SM_W + 24576, 4096, 512, 2);
      {
        uint4 v[2][4];
        mbar_wait(BAR(B_F2), 0);
        mbar_wait(BAR(B_F2 + 1), 0);
        WG_FENCE();
#pragma unroll
        for (int s = 0; s < 8; s++) {
          wgmma_ss_tb_n160(acc, dA0 + (s >> 2) * 1792 + (s & 3) * 2, dB0 + (s >> 2) * 1792 + (s & 3) * 64, s > 0);
          if (s == 3 || s == 5 || s == 7) WG_COMMIT();
          if (s == RQ0) { bar_sync(1, 128); red_ld(v, sb + SM_W + 24576, 8192, t128); }
          if (s == RQ1) red_st(v, sb + SM_D + 128 + 2 * TP, t128, 1);
          if (s == RQ2) { red_fin(BAR(B_ZR + 2), 1); TS(34); }
          if (s == 5) { WG_WAIT(1); if (lane == 0) mbar_arrive(BAR(B_E2)); }
        }
      }
      int s = G2P - 1, ph = 0, sp;
#pragma unroll 1
      for (int c = G2P; c < 24; c++) {
        sp = s;
        if (++s == 5 || c == 4) { s = 0; ph ^= 1; }
        const int pf = s == 4 ? ph ^ 1 : ph;
        const bool pend = __all_sync(0xffffffffu, mbar_test(BAR(B_F2 + s), pf));
        if (!pend) {
          WG_WAIT(0);
          if (lane == 0) mbar_arrive(BAR(B_E2 + sp));
          mbar_wait(BAR(B_F2 + s), pf);
        }
        const uint64_t dA = s == 4 ? dA4 : dA0 + s * 1792, dB = s == 4 ? dB4 : dB0 + s * 1792;
        TS(36 + (c >> 1));
        WG_FENCE();
#pragma unroll
        for (int kk = 0; kk < 4; kk++) wgmma_ss_tb_n160(acc, dA + kk * 2, dB + kk * 64, 1);
        WG_COMMIT();
        if (pend) { WG_WAIT(1); if (lane == 0) mbar_arrive(BAR(B_E2 + sp)); }
      }
      TS(11);
      mbar_wait(BAR(B_GA), 0);
      uint4 ga[10];
#pragma unroll
      for (int j = 0; j < 10; j++) ga[j] = ldsm4(og + j * 32);
      const float gv0 = __uint_as_float(lds32(sb + SM_GT + (16 * w + g) * 4)), gv1 = __uint_as_float(lds32(sb + SM_GT + (16 * w + g + 8) * 4));
      const uint32_t om0 = pack_bf16(1.0f - gv0, 1.0f - gv0), om1 = pack_bf16(1.0f - gv1, 1.0f - gv1);
      WG_WAIT(0);
      TS(12);
#pragma unroll
      for (int j = 0; j < 10; j++) {
        const uint32_t o0 = badd2(ga[j].x, bmul2(om0, pack_bf16(acc[8 * j + 0], acc[8 * j + 1])));
        const uint32_t o1 = badd2(ga[j].y, bmul2(om1, pack_bf16(acc[8 * j + 2], acc[8 * j + 3])));
        const uint32_t o2 = badd2(ga[j].z, bmul2(om0, pack_bf16(acc[8 * j + 4], acc[8 * j + 5])));
        const uint32_t o3 = badd2(ga[j].w, bmul2(om1, pack_bf16(acc[8 * j + 6], acc[8 * j + 7])));
        stsm4(og + j * 32, o0, o1, o2, o3);
      }
      TS(29);
      __syncwarp();
      {
        const uint32_t so = sb + SM_W + 2 * 24576 + w * (16 * 336) + lane * 16;
        uint8_t* go = P.out + (size_t)(rb * 64 + w * 16) * 1280 + cb * 320 + lane * 16;
        uint4 ov[10];
#pragma unroll
        for (int i = 0; i < 10; i++) ov[i] = lds128m(so + i * 512 + (((i * 32 + lane) * 3277) >> 16) * 16);
        TS(32);
#pragma unroll
        for (int i = 0; i < 10; i++) *(uint4*)(go + i * 512 + (((i * 32 + lane) * 3277) >> 16) * 960) = ov[i];
      }
      TS(13);
    } else {
      {
        uint4 v[2][4];
        bar_sync(2, 128);
        red_ld(v, sb + SM_W + 49152, 8192, t128);
        red_st(v, sb + SM_D + 128 + 4 * TP, t128, 1);
        red_fin(BAR(B_ZR + 4), 1);
      }
      TS(35);
      const uint32_t za = sb + SM_D + 16384 + ((lane & 7) + 8 * (lane >> 4)) * 128 + (((2 * w + ((lane >> 3) & 1)) ^ (lane & 7)) << 4);
      mbar_wait(BAR(B_ZR + 4), 0);
      mbar_wait(BAR(B_Q), 0);
      TS(10);
      uint4 zr[10], qr[10];
#pragma unroll
      for (int j = 0; j < 10; j++) { if (j < 8) zr[j] = ldsm4t(za + j * 2048); qr[j] = ldsm4(sb + (j < 8 ? SM_D + (j >> 1) * 4096 : SM_W + 45056) + (fo ^ ((j & 1) << 5))); }
      const float gv0 = __uint_as_float(lds32(sb + SM_GT + (16 * w + g) * 4)), gv1 = __uint_as_float(lds32(sb + SM_GT + (16 * w + g + 8) * 4));
      const uint32_t g0 = pack_bf16(gv0, gv0), g1 = pack_bf16(gv1, gv1);
#pragma unroll
      for (int j = 0; j < 10; j++) {
        if (j == 8) { mbar_wait(BAR(B_Q2), 0); TS(11); zr[8] = ldsm4t(za + 8 * 2048); zr[9] = ldsm4t(za + 9 * 2048); }
        stsm4(og + j * 32, bmul2(g0, bmul2(qr[j].x, zr[j].x)), bmul2(g1, bmul2(qr[j].y, zr[j].y)), bmul2(g0, bmul2(qr[j].z, zr[j].z)), bmul2(g1, bmul2(qr[j].w, zr[j].w)));
      }
      mbar_arrive(BAR(B_GA));
      TS(13);
    }
  }
}

typedef CUresult (*EncFn)(CUtensorMap*, CUtensorMapDataType, cuuint32_t, void*, const cuuint64_t*, const cuuint64_t*, const cuuint32_t*, const cuuint32_t*,
                          CUtensorMapInterleave, CUtensorMapSwizzle, CUtensorMapL2promotion, CUtensorMapFloatOOBfill);

void enc(EncFn fn, CUtensorMap* m, CUtensorMapDataType dt, int rank, const void* p, const cuuint64_t* gd, const cuuint64_t* gs, const cuuint32_t* bd, CUtensorMapSwizzle sw) {
  cuuint32_t es[5] = {1, 1, 1, 1, 1};
  fn(m, dt, rank, (void*)p, gd, gs, bd, es, CU_TENSOR_MAP_INTERLEAVE_NONE, sw, CU_TENSOR_MAP_L2_PROMOTION_L2_128B, CU_TENSOR_MAP_FLOAT_OOB_FILL_NONE);
}

}

extern "C" void kernel_launch(void* const* d_in, const int* in_sizes, int n_in, void* d_out, int out_size) {
  static EncFn fn = nullptr;
  static void *zp = nullptr, *xp = nullptr;
  if (!fn) {
    cudaGetSymbolAddress(&zp, g_z);
    cudaGetSymbolAddress(&xp, g_X);
    void* f = nullptr; cudaDriverEntryPointQueryResult qr;
    cudaGetDriverEntryPoint("cuTensorMapEncodeTiled", &f, cudaEnableDefault, &qr);
    fn = (EncFn)f;
    cudaFuncSetAttribute(fused_kernel, cudaFuncAttributeMaxDynamicSharedMemorySize, SM_TOTAL);
  }
  Maps m;
  const CUtensorMapDataType BF = CU_TENSOR_MAP_DATA_TYPE_BFLOAT16;
  { cuuint64_t gd[2] = {640, 2048}, gs[1] = {1280}; cuuint32_t bd[2] = {64, 128}; enc(fn, &m.x, BF, 2, d_in[0], gd, gs, bd, CU_TENSOR_MAP_SWIZZLE_128B); }
  { cuuint64_t gd[3] = {64, 640, 24}, gs[2] = {3072, 128}; cuuint32_t bd[3] = {64, 32, 3};
    enc(fn, &m.wg, BF, 3, d_in[7], gd, gs, bd, CU_TENSOR_MAP_SWIZZLE_128B); enc(fn, &m.wu, BF, 3, d_in[8], gd, gs, bd, CU_TENSOR_MAP_SWIZZLE_128B); }
  { cuuint64_t gd[3] = {32, 1536, 20}, gs[2] = {1280, 64}; cuuint32_t bd[3] = {32, 64, 4}; enc(fn, &m.wd, BF, 3, d_in[9], gd, gs, bd, CU_TENSOR_MAP_SWIZZLE_64B); }
  { cuuint64_t gd[3] = {32, 2048, 20}, gs[2] = {1280, 64}; cuuint32_t bk[3] = {32, 35, 2}, bv[3] = {32, 32, 2};
    enc(fn, &m.k, BF, 3, d_in[1], gd, gs, bk, CU_TENSOR_MAP_SWIZZLE_NONE); enc(fn, &m.v, BF, 3, d_in[2], gd, gs, bv, CU_TENSOR_MAP_SWIZZLE_NONE); }
  { cuuint64_t gd[5] = {1024, 16, 2, 2, 485}, gs[4] = {40960, 2048, 20480, 4096}; cuuint32_t bd[5] = {16, 16, 2, 2, 1}; enc(fn, &m.xs, BF, 5, xp, gd, gs, bd, CU_TENSOR_MAP_SWIZZLE_NONE); }
  { cuuint64_t gd[3] = {64, 16, 1280}, gs[2] = {128, 2048}; cuuint32_t bd[3] = {64, 18, 10}; enc(fn, &m.xl, BF, 3, xp, gd, gs, bd, CU_TENSOR_MAP_SWIZZLE_NONE); }
  { cuuint64_t gd[3] = {32, 2048, 20}, gs[2] = {1280, 64}; cuuint32_t bd[3] = {32, 64, 5}, bq[3] = {32, 64, 1};
    enc(fn, &m.q, BF, 3, d_in[0], gd, gs, bq, CU_TENSOR_MAP_SWIZZLE_64B); enc(fn, &m.o, BF, 3, d_out, gd, gs, bd, CU_TENSOR_MAP_SWIZZLE_64B); }
  { cuuint64_t gd[2] = {2048, 640}, gs[1] = {4096}; cuuint32_t bd[2] = {64, 32}; enc(fn, &m.z, BF, 2, zp, gd, gs, bd, CU_TENSOR_MAP_SWIZZLE_128B); }
  Ptrs p;
  p.out = (uint8_t*)d_out; p.x = (const __nv_bfloat16*)d_in[0]; p.shift_k = (const __nv_bfloat16*)d_in[3]; p.ssm_k = (const __nv_bfloat16*)d_in[4];
  p.ssm_D = (const __nv_bfloat16*)d_in[5]; p.gate_w = (const __nv_bfloat16*)d_in[10];
  p.wg = (const __nv_bfloat16*)d_in[7]; p.wu = (const __nv_bfloat16*)d_in[8];
  fused_kernel<<<128, 384, SM_TOTAL, cudaStreamPerThread>>>(m, p, 0u);
}
```

```cpp
#include <cuda_runtime.h>
#include <cuda_bf16.h>
#include <cuda.h>
#include <stdint.h>

namespace {

constexpr int XP = 2304;
constexpr int XCH = 2 * XP;
constexpr int TP = 8320;
#define KV0 3
#define KV1 4
#define KV2 5
#define KV3 6
#define KV4 7
#define NPRE 1
#define PD 10
#define PF0 10
#define LSTEP 0
#define WD_N 8
#define SK_N 9
#define MAP1 1
#define MAP2 1
#define SGB 8
#define HOFF 2
#define PF_N 14
#define X9_N 15
#define WK 5
#define SG0 40
#define QC 1
#define G2P 2
#define RP0 1
#define RP1 4
#define RP2 7
#define RQ0 1
#define RQ1 3
#define RQ2 6
#define SG1 4

#define RM 2
#define PER 320
#define TICK 1
#define TDEL 100
#define XS 7
#define XFIX 0
#define RS 5
#define EG 1
#define NOZ 0
#define ZP 0
#define PSP 3
__host__ __device__ constexpr int g2s(int c) { return c < XS ? c % 5 : (c - XS) % 6 == 0 ? 5 : (XS + (c - XS) % 6 - 1) % 5; }
__host__ __device__ constexpr int g2u(int c) { return c < XS ? c / 5 : (c - XS) / 6 + (g2s(c) < 5 ? (XS - g2s(c) + 4) / 5 : 0); }
constexpr uint32_t SM_W = 0;
constexpr uint32_t SM_X = 122880;
constexpr uint32_t SM_R2 = 73728;
constexpr uint32_t SM_D = 188416;
__host__ __device__ constexpr uint32_t g2a(int s) { return s < 4 ? SM_R2 + s * 28672 : s == 4 ? 65536 : SM_D + 24576; }
__host__ __device__ constexpr uint32_t g2b(int s) { return s < 4 ? SM_R2 + s * 28672 + 8192 : s == 4 ? 24576 : 45056; }
constexpr uint32_t SM_BAR = 231296;
constexpr uint32_t SM_GAP = 172032;
constexpr uint32_t SM_GT = SM_BAR + 592;
constexpr uint32_t SM_GO = SM_GT + 256;
constexpr uint32_t SM_TOTAL = SM_GO + 64;
enum { B_FX = 0  , B_FW = 3  , B_KV = 8  , B_F2 = 13  , B_WD = 27, B_XI = 19, B_HR = 20, B_HF = 21  , B_Z = 28  , B_F9 = 24, B_GF = 25, B_PRE = 26,
       B_EW = 30  , B_EX = 36  , B_G1 = 39, B_E2 = 42  , B_HC = 48, B_Q = 49, B_KD = 50, B_HS = 54  , B_ZR = 60  , B_GA = 65, B_PF = 66   };

__device__ __align__(1024) uint8_t g_X[640 * 4096];
__device__ __align__(1024) uint8_t g_h[2048 * 1536 * 2];
__device__ __align__(1024) uint8_t g_wd[1536 * 640 * 2];
__device__ __align__(1024) uint8_t g_z[640 * 4096];
__device__ __align__(1024) float g_gate[2048];
__device__ uint32_t g_cnt[45 * 32];
#define TS(i)
#define TS1(i)
#define TR(v)
#define TW(i, v)

struct Maps { CUtensorMap x, wg, wu, wd, k, v, q, o, z, xs, xl; };
struct Ptrs { uint8_t* out; const __nv_bfloat16 *x, *shift_k, *ssm_k, *ssm_D, *gate_w, *wg, *wu; };

__device__ __forceinline__ uint32_t clk() { uint32_t t; asm volatile("mov.u32 %0, %%clock;" : "=r"(t) :: "memory"); return t; }
__device__ __forceinline__ uint32_t smem_u32(const void* p) { return (uint32_t)__cvta_generic_to_shared(p); }
__device__ __forceinline__ bool elect_one() { uint32_t p; asm volatile("{.reg .pred P; elect.sync _|P, 0xffffffff; selp.u32 %0, 1, 0, P;}" : "=r"(p)); return p; }
__device__ __forceinline__ void mbar_init(uint32_t bar, uint32_t cnt) { asm volatile("mbarrier.init.shared::cta.b64 [%0], %1;" ::"r"(bar), "r"(cnt)); }
__device__ __forceinline__ void mbar_expect_tx(uint32_t bar, uint32_t bytes) { asm volatile("mbarrier.arrive.expect_tx.shared::cta.b64 _, [%0], %1;" ::"r"(bar), "r"(bytes) : "memory"); }
__device__ __forceinline__ void mbar_arrive(uint32_t bar) { asm volatile("mbarrier.arrive.shared::cta.b64 _, [%0];" ::"r"(bar) : "memory"); }
__device__ __forceinline__ void mbar_wait(uint32_t bar, uint32_t parity) {
  uint32_t ok;
  asm volatile("{.reg .pred p; mbarrier.try_wait.parity.shared::cta.b64 p, [%1], %2; selp.u32 %0,1,0,p;}" : "=r"(ok) : "r"(bar), "r"(parity) : "memory");
  if (!ok) {
    uint32_t it = 0;
    do {
      asm volatile("{.reg .pred p; mbarrier.try_wait.parity.shared::cta.b64 p, [%1], %2, 2000; selp.u32 %0,1,0,p;}" : "=r"(ok) : "r"(bar), "r"(parity) : "memory");
    } while (!ok && ++it < 100000u);
  }
}
__device__ __forceinline__ void flag_wait(const uint32_t* p, uint32_t target) {
  uint32_t v, it = 0;
  while (true) {
    asm volatile("ld.acquire.gpu.global.u32 %0, [%1];" : "=r"(v) : "l"(p) : "memory");
    if ((int)(v - target) >= 0) break;
    if (++it > 400000u) break;
    __nanosleep(20);
  }
  asm volatile("fence.proxy.async.global;" ::: "memory");
}
__device__ __forceinline__ void flag_add(uint32_t* p, uint32_t v) {
  asm volatile("red.release.gpu.global.add.u32 [%0], %1;" ::"l"(p), "r"(v) : "memory");
}
__device__ __forceinline__ void flag_add_relaxed(uint32_t* p, uint32_t v) {
  asm volatile("red.relaxed.gpu.global.add.u32 [%0], %1;" ::"l"(p), "r"(v) : "memory");
}
__device__ __forceinline__ bool mbar_test(uint32_t bar, uint32_t parity) {
  uint32_t ok;
  asm volatile("{.reg .pred p; mbarrier.test_wait.parity.shared::cta.b64 p, [%1], %2; selp.u32 %0,1,0,p;}" : "=r"(ok) : "r"(bar), "r"(parity) : "memory");
  return ok;
}
__device__ __forceinline__ void cp_async16(uint32_t dst, const void* src) { asm volatile("cp.async.cg.shared.global [%0], [%1], 16;" ::"r"(dst), "l"(src) : "memory"); }
__device__ __forceinline__ void tma2d(uint32_t dst, const CUtensorMap* m, uint32_t bar, int c0, int c1) {
  asm volatile("cp.async.bulk.tensor.2d.shared::cluster.global.mbarrier::complete_tx::bytes [%0], [%1, {%3,%4}], [%2];" ::"r"(dst), "l"(m), "r"(bar), "r"(c0), "r"(c1) : "memory");
}
__device__ __forceinline__ void tma3d(uint32_t dst, const CUtensorMap* m, uint32_t bar, int c0, int c1, int c2) {
  asm volatile("cp.async.bulk.tensor.3d.shared::cluster.global.mbarrier::complete_tx::bytes [%0], [%1, {%3,%4,%5}], [%2];" ::"r"(dst), "l"(m), "r"(bar), "r"(c0), "r"(c1), "r"(c2) : "memory");
}
__device__ __forceinline__ void tma3d_store(const CUtensorMap* m, uint32_t src, int c0, int c1, int c2) {
  asm volatile("cp.async.bulk.tensor.3d.global.shared::cta.bulk_group [%0, {%2,%3,%4}], [%1];" ::"l"(m), "r"(src), "r"(c0), "r"(c1), "r"(c2) : "memory");
}
__device__ __forceinline__ void bulk_g2s(uint32_t dst, const void* src, uint32_t bytes, uint32_t bar) {
  asm volatile("cp.async.bulk.shared::cluster.global.mbarrier::complete_tx::bytes [%0], [%1], %2, [%3];" ::"r"(dst), "l"(src), "r"(bytes), "r"(bar) : "memory");
}
__device__ __forceinline__ void bulk_s2g(void* dst, uint32_t src, uint32_t bytes) {
  asm volatile("cp.async.bulk.global.shared::cta.bulk_group [%0], [%1], %2;" ::"l"(dst), "r"(src), "r"(bytes) : "memory");
}
__device__ __forceinline__ void l2_prefetch(const void* src, uint32_t bytes) {
  asm volatile("cp.async.bulk.prefetch.L2.global [%0], %1;" ::"l"(src), "r"(bytes) : "memory");
}
__device__ __forceinline__ void tma3d_prefetch(const CUtensorMap* m, int c0, int c1, int c2) {
  asm volatile("cp.async.bulk.prefetch.tensor.3d.L2.global.tile [%0, {%1,%2,%3}];" ::"l"(m), "r"(c0), "r"(c1), "r"(c2) : "memory");
}
__device__ __forceinline__ void tmap_prefetch(const CUtensorMap* m) { asm volatile("prefetch.tensormap [%0];" ::"l"(m) : "memory"); }
__device__ __forceinline__ uint64_t mkdesc(uint32_t addr, uint32_t lbo, uint32_t sbo, uint32_t swz) {
  return (uint64_t)((addr & 0x3FFFF) >> 4) | ((uint64_t)(lbo >> 4) << 16) | ((uint64_t)(sbo >> 4) << 32) | ((uint64_t)swz << 62);
}
#define WG_FENCE() asm volatile("wgmma.fence.sync.aligned;" ::: "memory")
#define WG_COMMIT() asm volatile("wgmma.commit_group.sync.aligned;" ::: "memory")
#define WG_WAIT(n) asm volatile("wgmma.wait_group.sync.aligned " #n ";" ::: "memory")
__device__ __forceinline__ void bar_sync(int id, int n) { asm volatile("bar.sync %0, %1;" ::"r"(id), "r"(n) : "memory"); }
__device__ __forceinline__ void bar_arrive(int id, int n) { asm volatile("bar.arrive %0, %1;" ::"r"(id), "r"(n) : "memory"); }
__device__ __forceinline__ uint32_t pack_bf16(float lo, float hi) { uint32_t r; asm("cvt.rn.bf16x2.f32 %0, %1, %2;" : "=r"(r) : "f"(hi), "f"(lo)); return r; }
__device__ __forceinline__ uint32_t bmul2(uint32_t a, uint32_t b) { uint32_t r; asm("mul.rn.bf16x2 %0, %1, %2;" : "=r"(r) : "r"(a), "r"(b)); return r; }
__device__ __forceinline__ uint32_t badd2(uint32_t a, uint32_t b) { uint32_t r; asm("add.rn.bf16x2 %0, %1, %2;" : "=r"(r) : "r"(a), "r"(b)); return r; }
__device__ __forceinline__ uint32_t bfma2(uint32_t a, uint32_t b, uint32_t c) { uint32_t r; asm("fma.rn.bf16x2 %0, %1, %2, %3;" : "=r"(r) : "r"(a), "r"(b), "r"(c)); return r; }
__device__ __forceinline__ uint32_t lds32(uint32_t a) { uint32_t r; asm volatile("ld.shared.u32 %0, [%1];" : "=r"(r) : "r"(a)); return r; }
__device__ __forceinline__ uint32_t lds32v(uint32_t a) { uint32_t r; asm volatile("ld.shared.u32 %0, [%1];" : "=r"(r) : "r"(a) : "memory"); return r; }
__device__ __forceinline__ uint4 lds128(uint32_t a) { uint4 v; asm volatile("ld.shared.v4.u32 {%0,%1,%2,%3}, [%4];" : "=r"(v.x), "=r"(v.y), "=r"(v.z), "=r"(v.w) : "r"(a)); return v; }
__device__ __forceinline__ uint4 lds128m(uint32_t a) { uint4 v; asm volatile("ld.shared.v4.u32 {%0,%1,%2,%3}, [%4];" : "=r"(v.x), "=r"(v.y), "=r"(v.z), "=r"(v.w) : "r"(a) : "memory"); return v; }
__device__ __forceinline__ void sts128(uint32_t a, uint32_t x, uint32_t y, uint32_t z, uint32_t w) { asm volatile("st.shared.v4.u32 [%0], {%1,%2,%3,%4};" ::"r"(a), "r"(x), "r"(y), "r"(z), "r"(w) : "memory"); }
__device__ __forceinline__ void stsm4(uint32_t a, uint32_t x, uint32_t y, uint32_t z, uint32_t w) { asm volatile("stmatrix.sync.aligned.m8n8.x4.shared.b16 [%0], {%1,%2,%3,%4};" ::"r"(a), "r"(x), "r"(y), "r"(z), "r"(w) : "memory"); }
__device__ __forceinline__ void stsm4t(uint32_t a, uint32_t x, uint32_t y, uint32_t z, uint32_t w) { asm volatile("stmatrix.sync.aligned.m8n8.x4.trans.shared.b16 [%0], {%1,%2,%3,%4};" ::"r"(a), "r"(x), "r"(y), "r"(z), "r"(w) : "memory"); }
__device__ __forceinline__ uint4 ldsm4(uint32_t a) { uint4 v; asm volatile("ldmatrix.sync.aligned.m8n8.x4.shared.b16 {%0,%1,%2,%3}, [%4];" : "=r"(v.x), "=r"(v.y), "=r"(v.z), "=r"(v.w) : "r"(a) : "memory"); return v; }
__device__ __forceinline__ uint4 ldsm4t(uint32_t a) { uint4 v; asm volatile("ldmatrix.sync.aligned.m8n8.x4.trans.shared.b16 {%0,%1,%2,%3}, [%4];" : "=r"(v.x), "=r"(v.y), "=r"(v.z), "=r"(v.w) : "r"(a) : "memory"); return v; }
__device__ __forceinline__ void tanh_h(float& a) { asm volatile("{.reg .f32 t; mul.f32 t, %0, 0f3F000000; tanh.approx.f32 %0, t;}" : "+f"(a)); }
__device__ __forceinline__ uint32_t sig_fin(float lo, float hi, float h) {
  uint32_t r;
  asm volatile("{.reg .f32 a, b; fma.rn.f32 a, %1, %3, %3; fma.rn.f32 b, %2, %3, %3; cvt.rn.bf16x2.f32 %0, b, a;}" : "=r"(r) : "f"(lo), "f"(hi), "f"(h));
  return r;
}
template <int LO, int HI> __device__ __forceinline__ uint32_t sig_range(float* a, uint32_t* sg, uint32_t zz) {
  uint32_t dep = 0;
#pragma unroll
  for (int b = LO; b < HI; b += SGB) {
    const int e = b + SGB < HI ? b + SGB : HI;
#pragma unroll
    for (int i = 2 * b; i < 2 * e; i++) tanh_h(a[i]);
    const float h = __uint_as_float(0x3f000000u | (__float_as_uint(a[2 * e - 1]) & zz));
#pragma unroll
    for (int i = b; i < e; i++) { sg[i] = sig_fin(a[2 * i], a[2 * i + 1], h); dep |= sg[i]; }
  }
  return dep & zz;
}
__device__ __forceinline__ void fadd_v(float& a, float b) { asm volatile("add.f32 %0, %0, %1;" : "+f"(a) : "f"(b)); }

__device__ __forceinline__ void wgmma_ss_tb_n192(float* d, uint64_t da, uint64_t db, int sc) {
  asm volatile("{.reg .pred p; setp.ne.b32 p, %98, 0;\n"
   "wgmma.mma_async.sync.aligned.m64n192k16.f32.bf16.bf16 {%0,%1,%2,%3,%4,%5,%6,%7,%8,%9,%10,%11,%12,%13,%14,%15,%16,%17,%18,%19,%20,%21,%22,%23,%24,%25,%26,%27,%28,%29,%30,%31,%32,%33,%34,%35,%36,%37,%38,%39,%40,%41,%42,%43,%44,%45,%46,%47,%48,%49,%50,%51,%52,%53,%54,%55,%56,%57,%58,%59,%60,%61,%62,%63,%64,%65,%66,%67,%68,%69,%70,%71,%72,%73,%74,%75,%76,%77,%78,%79,%80,%81,%82,%83,%84,%85,%86,%87,%88,%89,%90,%91,%92,%93,%94,%95}, %96, %97, p, 1, 1, 0, 1;}\n"
   : "+f"(d[0]),"+f"(d[1]),"+f"(d[2]),"+f"(d[3]),"+f"(d[4]),"+f"(d[5]),"+f"(d[6]),"+f"(d[7]),"+f"(d[8]),"+f"(d[9]),"+f"(d[10]),"+f"(d[11]),"+f"(d[12]),"+f"(d[13]),"+f"(d[14]),"+f"(d[15]),"+f"(d[16]),"+f"(d[17]),"+f"(d[18]),"+f"(d[19]),"+f"(d[20]),"+f"(d[21]),"+f"(d[22]),"+f"(d[23]),"+f"(d[24]),"+f"(d[25]),"+f"(d[26]),"+f"(d[27]),"+f"(d[28]),"+f"(d[29]),"+f"(d[30]),"+f"(d[31]),"+f"(d[32]),"+f"(d[33]),"+f"(d[34]),"+f"(d[35]),"+f"(d[36]),"+f"(d[37]),"+f"(d[38]),"+f"(d[39]),"+f"(d[40]),"+f"(d[41]),"+f"(d[42]),"+f"(d[43]),"+f"(d[44]),"+f"(d[45]),"+f"(d[46]),"+f"(d[47]),"+f"(d[48]),"+f"(d[49]),"+f"(d[50]),"+f"(d[51]),"+f"(d[52]),"+f"(d[53]),"+f"(d[54]),"+f"(d[55]),"+f"(d[56]),"+f"(d[57]),"+f"(d[58]),"+f"(d[59]),"+f"(d[60]),"+f"(d[61]),"+f"(d[62]),"+f"(d[63]),"+f"(d[64]),"+f"(d[65]),"+f"(d[66]),"+f"(d[67]),"+f"(d[68]),"+f"(d[69]),"+f"(d[70]),"+f"(d[71]),"+f"(d[72]),"+f"(d[73]),"+f"(d[74]),"+f"(d[75]),"+f"(d[76]),"+f"(d[77]),"+f"(d[78]),"+f"(d[79]),"+f"(d[80]),"+f"(d[81]),"+f"(d[82]),"+f"(d[83]),"+f"(d[84]),"+f"(d[85]),"+f"(d[86]),"+f"(d[87]),"+f"(d[88]),"+f"(d[89]),"+f"(d[90]),"+f"(d[91]),"+f"(d[92]),"+f"(d[93]),"+f"(d[94]),"+f"(d[95]) : "l"(da), "l"(db), "r"(sc));
}
__device__ __forceinline__ void wgmma_ss_tb_n160(float* d, uint64_t da, uint64_t db, int sc) {
  asm volatile("{.reg .pred p; setp.ne.b32 p, %82, 0;\n"
   "wgmma.mma_async.sync.aligned.m64n160k16.f32.bf16.bf16 {%0,%1,%2,%3,%4,%5,%6,%7,%8,%9,%10,%11,%12,%13,%14,%15,%16,%17,%18,%19,%20,%21,%22,%23,%24,%25,%26,%27,%28,%29,%30,%31,%32,%33,%34,%35,%36,%37,%38,%39,%40,%41,%42,%43,%44,%45,%46,%47,%48,%49,%50,%51,%52,%53,%54,%55,%56,%57,%58,%59,%60,%61,%62,%63,%64,%65,%66,%67,%68,%69,%70,%71,%72,%73,%74,%75,%76,%77,%78,%79}, %80, %81, p, 1, 1, 0, 1;}\n"
   : "+f"(d[0]),"+f"(d[1]),"+f"(d[2]),"+f"(d[3]),"+f"(d[4]),"+f"(d[5]),"+f"(d[6]),"+f"(d[7]),"+f"(d[8]),"+f"(d[9]),"+f"(d[10]),"+f"(d[11]),"+f"(d[12]),"+f"(d[13]),"+f"(d[14]),"+f"(d[15]),"+f"(d[16]),"+f"(d[17]),"+f"(d[18]),"+f"(d[19]),"+f"(d[20]),"+f"(d[21]),"+f"(d[22]),"+f"(d[23]),"+f"(d[24]),"+f"(d[25]),"+f"(d[26]),"+f"(d[27]),"+f"(d[28]),"+f"(d[29]),"+f"(d[30]),"+f"(d[31]),"+f"(d[32]),"+f"(d[33]),"+f"(d[34]),"+f"(d[35]),"+f"(d[36]),"+f"(d[37]),"+f"(d[38]),"+f"(d[39]),"+f"(d[40]),"+f"(d[41]),"+f"(d[42]),"+f"(d[43]),"+f"(d[44]),"+f"(d[45]),"+f"(d[46]),"+f"(d[47]),"+f"(d[48]),"+f"(d[49]),"+f"(d[50]),"+f"(d[51]),"+f"(d[52]),"+f"(d[53]),"+f"(d[54]),"+f"(d[55]),"+f"(d[56]),"+f"(d[57]),"+f"(d[58]),"+f"(d[59]),"+f"(d[60]),"+f"(d[61]),"+f"(d[62]),"+f"(d[63]),"+f"(d[64]),"+f"(d[65]),"+f"(d[66]),"+f"(d[67]),"+f"(d[68]),"+f"(d[69]),"+f"(d[70]),"+f"(d[71]),"+f"(d[72]),"+f"(d[73]),"+f"(d[74]),"+f"(d[75]),"+f"(d[76]),"+f"(d[77]),"+f"(d[78]),"+f"(d[79]) : "l"(da), "l"(db), "r"(sc));
}
__device__ __forceinline__ void wgmma_rs_tb_n192(float* d, const uint4& a, uint64_t db, int sc) {
  asm volatile("{.reg .pred p; setp.ne.b32 p, %101, 0;\n"
   "wgmma.mma_async.sync.aligned.m64n192k16.f32.bf16.bf16 {%0,%1,%2,%3,%4,%5,%6,%7,%8,%9,%10,%11,%12,%13,%14,%15,%16,%17,%18,%19,%20,%21,%22,%23,%24,%25,%26,%27,%28,%29,%30,%31,%32,%33,%34,%35,%36,%37,%38,%39,%40,%41,%42,%43,%44,%45,%46,%47,%48,%49,%50,%51,%52,%53,%54,%55,%56,%57,%58,%59,%60,%61,%62,%63,%64,%65,%66,%67,%68,%69,%70,%71,%72,%73,%74,%75,%76,%77,%78,%79,%80,%81,%82,%83,%84,%85,%86,%87,%88,%89,%90,%91,%92,%93,%94,%95}, {%96,%97,%98,%99}, %100, p, 1, 1, 1;}\n"
   : "+f"(d[0]),"+f"(d[1]),"+f"(d[2]),"+f"(d[3]),"+f"(d[4]),"+f"(d[5]),"+f"(d[6]),"+f"(d[7]),"+f"(d[8]),"+f"(d[9]),"+f"(d[10]),"+f"(d[11]),"+f"(d[12]),"+f"(d[13]),"+f"(d[14]),"+f"(d[15]),"+f"(d[16]),"+f"(d[17]),"+f"(d[18]),"+f"(d[19]),"+f"(d[20]),"+f"(d[21]),"+f"(d[22]),"+f"(d[23]),"+f"(d[24]),"+f"(d[25]),"+f"(d[26]),"+f"(d[27]),"+f"(d[28]),"+f"(d[29]),"+f"(d[30]),"+f"(d[31]),"+f"(d[32]),"+f"(d[33]),"+f"(d[34]),"+f"(d[35]),"+f"(d[36]),"+f"(d[37]),"+f"(d[38]),"+f"(d[39]),"+f"(d[40]),"+f"(d[41]),"+f"(d[42]),"+f"(d[43]),"+f"(d[44]),"+f"(d[45]),"+f"(d[46]),"+f"(d[47]),"+f"(d[48]),"+f"(d[49]),"+f"(d[50]),"+f"(d[51]),"+f"(d[52]),"+f"(d[53]),"+f"(d[54]),"+f"(d[55]),"+f"(d[56]),"+f"(d[57]),"+f"(d[58]),"+f"(d[59]),"+f"(d[60]),"+f"(d[61]),"+f"(d[62]),"+f"(d[63]),"+f"(d[64]),"+f"(d[65]),"+f"(d[66]),"+f"(d[67]),"+f"(d[68]),"+f"(d[69]),"+f"(d[70]),"+f"(d[71]),"+f"(d[72]),"+f"(d[73]),"+f"(d[74]),"+f"(d[75]),"+f"(d[76]),"+f"(d[77]),"+f"(d[78]),"+f"(d[79]),"+f"(d[80]),"+f"(d[81]),"+f"(d[82]),"+f"(d[83]),"+f"(d[84]),"+f"(d[85]),"+f"(d[86]),"+f"(d[87]),"+f"(d[88]),"+f"(d[89]),"+f"(d[90]),"+f"(d[91]),"+f"(d[92]),"+f"(d[93]),"+f"(d[94]),"+f"(d[95]) : "r"(a.x), "r"(a.y), "r"(a.z), "r"(a.w), "l"(db), "r"(sc));
}
template<int N> __device__ __forceinline__ void wgmma_rs(float* d, const uint32_t* a, uint64_t db, int sc);
template<> __device__ __forceinline__ void wgmma_rs<128>(float* d, const uint32_t* a, uint64_t db, int sc) {
  asm volatile("{.reg .pred p; setp.ne.b32 p, %69, 0;\n"
   "wgmma.mma_async.sync.aligned.m64n128k16.f32.bf16.bf16 {%0,%1,%2,%3,%4,%5,%6,%7,%8,%9,%10,%11,%12,%13,%14,%15,%16,%17,%18,%19,%20,%21,%22,%23,%24,%25,%26,%27,%28,%29,%30,%31,%32,%33,%34,%35,%36,%37,%38,%39,%40,%41,%42,%43,%44,%45,%46,%47,%48,%49,%50,%51,%52,%53,%54,%55,%56,%57,%58,%59,%60,%61,%62,%63}, {%64,%65,%66,%67}, %68, p, 1, 1, 0;}\n"
   : "+f"(d[0]),"+f"(d[1]),"+f"(d[2]),"+f"(d[3]),"+f"(d[4]),"+f"(d[5]),"+f"(d[6]),"+f"(d[7]),"+f"(d[8]),"+f"(d[9]),"+f"(d[10]),"+f"(d[11]),"+f"(d[12]),"+f"(d[13]),"+f"(d[14]),"+f"(d[15]),"+f"(d[16]),"+f"(d[17]),"+f"(d[18]),"+f"(d[19]),"+f"(d[20]),"+f"(d[21]),"+f"(d[22]),"+f"(d[23]),"+f"(d[24]),"+f"(d[25]),"+f"(d[26]),"+f"(d[27]),"+f"(d[28]),"+f"(d[29]),"+f"(d[30]),"+f"(d[31]),"+f"(d[32]),"+f"(d[33]),"+f"(d[34]),"+f"(d[35]),"+f"(d[36]),"+f"(d[37]),"+f"(d[38]),"+f"(d[39]),"+f"(d[40]),"+f"(d[41]),"+f"(d[42]),"+f"(d[43]),"+f"(d[44]),"+f"(d[45]),"+f"(d[46]),"+f"(d[47]),"+f"(d[48]),"+f"(d[49]),"+f"(d[50]),"+f"(d[51]),"+f"(d[52]),"+f"(d[53]),"+f"(d[54]),"+f"(d[55]),"+f"(d[56]),"+f"(d[57]),"+f"(d[58]),"+f"(d[59]),"+f"(d[60]),"+f"(d[61]),"+f"(d[62]),"+f"(d[63]) : "r"(a[0]), "r"(a[1]), "r"(a[2]), "r"(a[3]), "l"(db), "r"(sc));
}
template<> __device__ __forceinline__ void wgmma_rs<96>(float* d, const uint32_t* a, uint64_t db, int sc) {
  asm volatile("{.reg .pred p; setp.ne.b32 p, %53, 0;\n"
   "wgmma.mma_async.sync.aligned.m64n96k16.f32.bf16.bf16 {%0,%1,%2,%3,%4,%5,%6,%7,%8,%9,%10,%11,%12,%13,%14,%15,%16,%17,%18,%19,%20,%21,%22,%23,%24,%25,%26,%27,%28,%29,%30,%31,%32,%33,%34,%35,%36,%37,%38,%39,%40,%41,%42,%43,%44,%45,%46,%47}, {%48,%49,%50,%51}, %52, p, 1, 1, 0;}\n"
   : "+f"(d[0]),"+f"(d[1]),"+f"(d[2]),"+f"(d[3]),"+f"(d[4]),"+f"(d[5]),"+f"(d[6]),"+f"(d[7]),"+f"(d[8]),"+f"(d[9]),"+f"(d[10]),"+f"(d[11]),"+f"(d[12]),"+f"(d[13]),"+f"(d[14]),"+f"(d[15]),"+f"(d[16]),"+f"(d[17]),"+f"(d[18]),"+f"(d[19]),"+f"(d[20]),"+f"(d[21]),"+f"(d[22]),"+f"(d[23]),"+f"(d[24]),"+f"(d[25]),"+f"(d[26]),"+f"(d[27]),"+f"(d[28]),"+f"(d[29]),"+f"(d[30]),"+f"(d[31]),"+f"(d[32]),"+f"(d[33]),"+f"(d[34]),"+f"(d[35]),"+f"(d[36]),"+f"(d[37]),"+f"(d[38]),"+f"(d[39]),"+f"(d[40]),"+f"(d[41]),"+f"(d[42]),"+f"(d[43]),"+f"(d[44]),"+f"(d[45]),"+f"(d[46]),"+f"(d[47]) : "r"(a[0]), "r"(a[1]), "r"(a[2]), "r"(a[3]), "l"(db), "r"(sc));
}
template<> __device__ __forceinline__ void wgmma_rs<64>(float* d, const uint32_t* a, uint64_t db, int sc) {
  asm volatile("{.reg .pred p; setp.ne.b32 p, %37, 0;\n"
   "wgmma.mma_async.sync.aligned.m64n64k16.f32.bf16.bf16 {%0,%1,%2,%3,%4,%5,%6,%7,%8,%9,%10,%11,%12,%13,%14,%15,%16,%17,%18,%19,%20,%21,%22,%23,%24,%25,%26,%27,%28,%29,%30,%31}, {%32,%33,%34,%35}, %36, p, 1, 1, 0;}\n"
   : "+f"(d[0]),"+f"(d[1]),"+f"(d[2]),"+f"(d[3]),"+f"(d[4]),"+f"(d[5]),"+f"(d[6]),"+f"(d[7]),"+f"(d[8]),"+f"(d[9]),"+f"(d[10]),"+f"(d[11]),"+f"(d[12]),"+f"(d[13]),"+f"(d[14]),"+f"(d[15]),"+f"(d[16]),"+f"(d[17]),"+f"(d[18]),"+f"(d[19]),"+f"(d[20]),"+f"(d[21]),"+f"(d[22]),"+f"(d[23]),"+f"(d[24]),"+f"(d[25]),"+f"(d[26]),"+f"(d[27]),"+f"(d[28]),"+f"(d[29]),"+f"(d[30]),"+f"(d[31]) : "r"(a[0]), "r"(a[1]), "r"(a[2]), "r"(a[3]), "l"(db), "r"(sc));
}
template<> __device__ __forceinline__ void wgmma_rs<32>(float* d, const uint32_t* a, uint64_t db, int sc) {
  asm volatile("{.reg .pred p; setp.ne.b32 p, %21, 0;\n"
   "wgmma.mma_async.sync.aligned.m64n32k16.f32.bf16.bf16 {%0,%1,%2,%3,%4,%5,%6,%7,%8,%9,%10,%11,%12,%13,%14,%15}, {%16,%17,%18,%19}, %20, p, 1, 1, 0;}\n"
   : "+f"(d[0]),"+f"(d[1]),"+f"(d[2]),"+f"(d[3]),"+f"(d[4]),"+f"(d[5]),"+f"(d[6]),"+f"(d[7]),"+f"(d[8]),"+f"(d[9]),"+f"(d[10]),"+f"(d[11]),"+f"(d[12]),"+f"(d[13]),"+f"(d[14]),"+f"(d[15]) : "r"(a[0]), "r"(a[1]), "r"(a[2]), "r"(a[3]), "l"(db), "r"(sc));
}

__device__ __forceinline__ void conv_dupA(uint32_t* A, uint32_t zz) {
#pragma unroll
  for (int s = 0; s < 4; s++) {
    asm volatile("xor.b32 %0, %1, %2;" : "=r"(A[4 * s + 3]) : "r"(A[4 * s]), "r"(zz));
    if (s < 3) asm volatile("xor.b32 %0, %1, %2;" : "=r"(A[4 * s + 6]) : "r"(A[4 * s + 1]), "r"(zz));
  }
}
template <int OFF, int DUP = 1> __device__ __forceinline__ void conv_ldA(uint32_t* A, uint32_t ra, uint32_t zz) {
  A[2] = lds32(ra + OFF);
#pragma unroll
  for (int s = 0; s < 4; s++) { A[4 * s] = lds32(ra + OFF + 32 * s + 16); A[4 * s + 1] = lds32(ra + OFF + 32 * s + 32); }
  if (DUP) conv_dupA(A, zz);
}
template <int N, int H, int ACC = 0> __device__ __forceinline__ void conv_grp(float* T, const uint32_t* A, uint64_t dX) {
  WG_FENCE();
#pragma unroll
  for (int s = 0; s < 4; s++) wgmma_rs<N>(T, A + 4 * s, dX - (4 * H + s), (ACC || H > 0 || s > 0));
  WG_COMMIT();
}
template <int H> __device__ __forceinline__ void conv_grp2(float* T, float* U, const uint32_t* A, uint64_t dX) {
  WG_FENCE();
#pragma unroll
  for (int s = 0; s < 4; s++) {
    wgmma_rs<64>(T, A + 4 * s, dX + 32 - (4 * H + s), (H > 0 || s > 0));
    wgmma_rs<32>(U, A + 4 * s, dX - (4 * H + s), (H > 0 || s > 0));
  }
  WG_COMMIT();
}

__device__ __forceinline__ void red_ld(uint4 (*v)[4], uint32_t pb, int idx) {
#pragma unroll
  for (int n = 0; n < 2; n++)
#pragma unroll
    for (int q = 0; q < 4; q++) { v[n][q] = make_uint4(0, 0, 0, 0); if (n > 0 || idx >= 16 * q) v[n][q] = lds128(pb + idx * 16 + q * 3840 + n * 2048); }
}
__device__ __forceinline__ void red_st(const uint4 (*v)[4], uint32_t zo, int idx) {
#pragma unroll
  for (int m = 0; m < 2; m++)
    sts128(zo + idx * 16 + m * 2048, badd2(badd2(v[m][0].x, v[m][1].x), badd2(v[m][2].x, v[m][3].x)), badd2(badd2(v[m][0].y, v[m][1].y), badd2(v[m][2].y, v[m][3].y)),
           badd2(badd2(v[m][0].z, v[m][1].z), badd2(v[m][2].z, v[m][3].z)), badd2(badd2(v[m][0].w, v[m][1].w), badd2(v[m][2].w, v[m][3].w)));
}
__device__ __forceinline__ void red_fin(uint32_t bar) {
  asm volatile("fence.proxy.async.shared::cta;" ::: "memory");
  mbar_arrive(bar);
}

__global__ void __launch_bounds__(384, 1) fused_kernel(const __grid_constant__ Maps maps, const Ptrs P, const uint32_t zz) {
  extern __shared__ __align__(1024) uint8_t smem[];
  constexpr uint32_t sb = 1024;
  const int tid = threadIdx.x;
  const int b = blockIdx.x;
  const uint32_t bars = sb + SM_BAR;

#define BAR(i) (bars + 8u * (i))
  TR(t63);
  const int rt = (b >> 1) & 15, ct = (b & 1) | ((b >> 5) << 1);
  const int rb = b >> 2, cb = b & 3;
  const int b2 = cb * 32 + rb;
  const int ch0 = cb * 160 + rb;

  if ((tid >> 5) == 8) {
    if (elect_one()) {
      mbar_init(BAR(B_FX), 1); mbar_init(BAR(B_FW), 1); mbar_init(BAR(B_FW + 1), 1);
      asm volatile("fence.proxy.async.shared::cta;" ::: "memory");
      mbar_expect_tx(BAR(B_FX), 16384); tma2d(sb + SM_X, &maps.x, BAR(B_FX), 0, rt * 128);
#pragma unroll
      for (int n = 0; n < NPRE; n++) {
        mbar_expect_tx(BAR(B_FW + n), 24576);
        tma3d(sb + SM_W + n * 24576, &maps.wg, BAR(B_FW + n), 0, n * 32, ct * 3); tma3d(sb + SM_W + n * 24576 + 12288, &maps.wu, BAR(B_FW + n), 0, n * 32, ct * 3);
      }
      mbar_init(BAR(B_FX + 1), 1); mbar_init(BAR(B_FX + 2), 1); mbar_init(BAR(B_FW + 2), 1);
      asm volatile("fence.proxy.async.shared::cta;" ::: "memory");
    }
  }
  const int wg = __shfl_sync(0xffffffffu, tid >> 7, 0);

  if (wg == 2) {
    asm volatile("setmaxnreg.dec.sync.aligned.u32 40;");
    bar_sync(0, 384);
    const int warp = __shfl_sync(0xffffffffu, tid >> 5, 0) - 8, lane = tid & 31;
    if (warp == 0) {
      if (elect_one()) {
        TS1(11); TW(9, t9); TW(10, t10);
#pragma unroll
        for (int n = NPRE; n < 20; n++) {
          const int k = n < 14 ? (n >> 1) : n < 17 ? n - 7 : n - 10;
          const bool up = n < 14 ? (n & 1) : (n >= 17);
          if (n == PF_N) { tma3d_prefetch(&maps.wu, 0, 576, ct * 3); tma3d_prefetch(&maps.wu, 0, 608, ct * 3); }
          if (!up && n != 16) {
            const int xs = k % 3;
            if (k >= 3) mbar_wait(BAR(B_EX + xs), ((k / 3) - 1) & 1);
            mbar_expect_tx(BAR(B_FX + xs), 16384);
            tma2d(sb + SM_X + xs * 16384, &maps.x, BAR(B_FX + xs), k * 64, rt * 128);
          }
          const int s = n % 5;
          if (n >= 5) mbar_wait(BAR(B_EW + s), ((n / 5) - 1) & 1);
          mbar_expect_tx(BAR(B_FW + s), 24576);
          tma3d(sb + SM_W + s * 24576, n >= 17 ? &maps.wu : &maps.wg, BAR(B_FW + s), 0, n < 14 ? n * 32 : k * 64, ct * 3);
          tma3d(sb + SM_W + s * 24576 + 12288, n < 14 || n >= 17 ? &maps.wu : &maps.wg, BAR(B_FW + s), 0, n < 14 ? n * 32 : k * 64 + 32, ct * 3);
          if (n == X9_N) {
            mbar_wait(BAR(B_GF), 0);
            TS1(33);
            mbar_expect_tx(BAR(B_F9), 16384);
            tma2d(sb + SM_GAP, &maps.x, BAR(B_F9), 576, rt * 128);
          }
          if (n == KV0 || n == KV1 || n == KV2 || n == KV3 || n == KV4) {
            const int r = n == KV0 ? 0 : n == KV1 ? 1 : n == KV2 ? 2 : n == KV3 ? 3 : 4;
            mbar_expect_tx(BAR(B_KV + r), 8576);
            tma3d(sb + SM_D + r * 8576, &maps.k, BAR(B_KV + r), 0, (b >> 1) * 32 - 3, (b & 1) * 10 + 2 * r);
            tma3d(sb + SM_D + r * 8576 + 4480, &maps.v, BAR(B_KV + r), 0, (b >> 1) * 32, (b & 1) * 10 + 2 * r);
          }
          if (n >= SK_N && n < SK_N + 5) l2_prefetch(P.ssm_k + (size_t)(ch0 + 32 * (n - SK_N)) * 2048, 4096);
          if (n == WD_N) {
            mbar_expect_tx(BAR(B_WD), b < 120 ? 16384 : 0);
            if (b < 120) tma3d(sb + SM_GAP, &maps.wd, BAR(B_WD), 0, (b / 5) * 64, (b % 5) * 4);
          }
        }
        TS1(32);
        mbar_wait(BAR(B_PRE), 0);
        const uint32_t target = lds32v(sb + SM_BAR + 576);
        mbar_wait(BAR(B_EW + 0), 1);
        flag_wait(&g_cnt[0], target);
        mbar_expect_tx(BAR(B_XI), 5 * XCH);
        tma3d(sb + SM_W, &maps.xl, BAR(B_XI), 0, -2, b2 * 10);
        TS1(1);
        const uint8_t* wsrc = g_wd + cb * 20480;
        mbar_wait(BAR(B_G1), 0);
        for (int s = 0; s < 4; s++) {
          mbar_expect_tx(BAR(B_F2 + s), 28672);
          bulk_g2s(sb + SM_R2 + s * 28672 + 8192, wsrc + s * 81920, 20480, BAR(B_F2 + s));
        }
        TS1(2);
        flag_wait(&g_cnt[(1 + rb) * 32], target);
        TS1(3);
        const uint8_t* hsrc = g_h + (size_t)rb * 24 * 8192;
        for (int s = 0; s < 4; s++) {
          if (!(s & 1)) mbar_wait(BAR(B_KV + (s >> 1)), 1);
          bulk_g2s(sb + SM_R2 + s * 28672, hsrc + s * 8192, 8192, BAR(B_F2 + s));
        }
        mbar_expect_tx(BAR(B_Q), 256);
        bulk_g2s(sb + SM_GT, g_gate + rb * 64, 256, BAR(B_Q));
        tmap_prefetch(&maps.z);
        {
          constexpr int R1 = 24 - XFIX;
          uint32_t tick = 0;
          int cc = 4;
#pragma unroll
          for (int c = 4; c < 24; c++) {
            if (XFIX && c == XS) continue;
            const int s = g2s(c);
            const uint8_t* pa = hsrc + cc * 8192;
            const uint8_t* pw = wsrc + cc * 81920;
            if (c == 4) { mbar_wait(BAR(B_HF + 1), 0); if (RM > 2) mbar_wait(BAR(B_KV + 2), 1); else mbar_wait(BAR(B_ZR + 2), 0); }
            else if (c == XS) mbar_wait(BAR(B_KV + 3), 1);
            else mbar_wait(BAR(B_E2 + s), (g2u(c) - 1) & 1);
            mbar_expect_tx(BAR(B_F2 + s), 28672);
            if (c == RS) {
              const uint32_t q = (clk() + TDEL) / PER + TICK;
              tick = q * PER; cc = RS + q % (R1 - RS);
              pa = hsrc + cc * 8192; pw = wsrc + cc * 81920;
            }
            if (TICK && c >= RS) { for (int it = 0; (int)(clk() - tick) < 0 && it < 200; it++) {} tick += PER; }
            bulk_g2s(sb + g2b(s), pw, 20480, BAR(B_F2 + s));
            bulk_g2s(sb + g2a(s), pa, 8192, BAR(B_F2 + s));
            if (++cc == R1) cc = RS;
          }
        }
        TS1(4);
      }
    } else {
      const int hw = warp - 1;
      if (hw == 2) {
        if (smem_u32(smem) != sb) asm volatile("trap;");
        const int c8 = lane & 7, r4 = lane >> 3;
        float acc[4] = {0.f, 0.f, 0.f, 0.f};
        uint4 gw = __ldg((const uint4*)(P.gate_w + c8 * 8));
        gw.x |= __ldg((const uint32_t*)(P.gate_w + 128 + lane * 16)) & zz;
        uint32_t xs = 0, xph = 0;
        const __nv_bfloat16* pw = (lane & 1 ? P.wu : P.wg) + (rt * 4 + (lane >> 3)) * 1536 + ct * 192 + ((lane >> 1) & 3) * 64;
        const __nv_bfloat16* px = P.x + (rt * 128 + ct * 16 + (lane & 15)) * 640;
        const bool pfw = (lane & 6) != 6;
#define PFK(kk) { if (pfw) asm volatile("prefetch.global.L2 [%0];" ::"l"(pw + (kk) * 98304)); if (lane < 16) asm volatile("prefetch.global.L2 [%0];" ::"l"(px + (kk) * 64)); }
        for (int k = PF0; k < PD; k++) PFK(k)
#pragma unroll 1
        for (int k = 0; k < 10; k++) {
          const uint4 gn = __ldg((const uint4*)(P.gate_w + (k < 9 ? k + 1 : 0) * 64 + c8 * 8));
          if (k == 9) { xs = 3; mbar_wait(BAR(B_F9), 0); } else mbar_wait(BAR(B_FX + xs), xph);
          if (k + PD < 10) PFK(k + PD)
#pragma unroll
          for (int i = 0; i < 4; i++) {
            const int row = (i >> 1) * 64 + ct * 8 + (i & 1) * 4 + r4;
            const uint4 v = lds128(sb + SM_X + xs * 16384 + row * 128 + ((c8 ^ (row & 7)) << 4));
            const uint32_t p[4] = {bmul2(v.x, gw.x), bmul2(v.y, gw.y), bmul2(v.z, gw.z), bmul2(v.w, gw.w)};
#pragma unroll
            for (int e = 0; e < 4; e++) acc[i] += __uint_as_float(p[e] << 16) + __uint_as_float(p[e] & 0xffff0000u);
          }
          __syncwarp();
          if (lane == 0 && k < 6) mbar_arrive(BAR(B_EX + xs));
          if (lane == 0 && k == WK) {
            mbar_wait(BAR(B_WD), 0);
            if (b < 120) bulk_s2g(g_wd + (size_t)b * 16384, sb + SM_GAP, 16384);
            asm volatile("cp.async.bulk.commit_group;" ::: "memory");
          }
          if (lane == 0 && k == WK + 1) {
            asm volatile("cp.async.bulk.wait_group 0;" ::: "memory");
            mbar_arrive(BAR(B_GF));
          }
          __syncwarp();
          if (++xs == 3) { xs = 0; xph ^= 1; }
          gw = gn;
        }
#pragma unroll
        for (int i = 0; i < 4; i++)
#pragma unroll
          for (int o = 1; o < 8; o <<= 1) acc[i] += __shfl_xor_sync(0xffffffffu, acc[i], o);
        if (c8 < 4) {
          const float sv = c8 == 0 ? acc[0] : c8 == 1 ? acc[1] : c8 == 2 ? acc[2] : acc[3];
          const float l = __bfloat162float(__float2bfloat16_rn(sv));
          const float gv = __bfloat162float(__float2bfloat16_rn(1.0f / (1.0f + __expf(-l))));
          asm volatile("st.shared.f32 [%0], %1;" ::"r"(sb + SM_GO + c8 * 16 + r4 * 4), "f"(gv) : "memory");
          asm volatile("fence.proxy.async.shared::cta;" ::: "memory");
        }
        __syncwarp();
        if (lane == 0) { mbar_arrive(BAR(B_G1)); mbar_arrive(BAR(B_HS + 0)); mbar_arrive(BAR(B_HS + 1)); TS1(7); }
      } else {
        const int ht = tid - 288;
        const int rc = b >> 1, chb = (b & 1) * 320;
        const int cl = hw * 32 + (lane >> 1) * 2;
        const __nv_bfloat16* skp = P.shift_k + (chb + cl) * 4;
        uint4 sk = __ldg((const uint4*)skp);
        if (ht < 20) asm volatile("prefetch.global.L2 [%0];" ::"l"(P.shift_k + chb * 4 + ht * 64));
        uint32_t ka = sb + SM_D + hw * 2240 + (lane >> 1) * 4 + (lane & 1) * 1024;
        const uint32_t vo = 4480 - hw * 192, so = 4480 - hw * 192 + (lane >> 1) * 28 - (lane & 1) * 1008;
#pragma unroll 1
        for (int pg = 0; pg < 5; pg++) {
          const uint32_t w0 = __byte_perm(sk.x, sk.z, 0x5410), w1 = __byte_perm(sk.x, sk.z, 0x7632);
          const uint32_t w2 = __byte_perm(sk.y, sk.w, 0x5410), w3 = __byte_perm(sk.y, sk.w, 0x7632);
          sk = __ldg((const uint4*)(skp + (pg < 4 ? pg + 1 : 0) * 256));
          mbar_wait(BAR(B_KV + pg), 0);
          if (ht == 0) TS1(21 + pg);
          uint32_t kk[19], o[8];
#pragma unroll
          for (int i = 0; i < 11; i++) kk[i] = lds32(ka + i * 64);
#pragma unroll
          for (int h = 0; h < 2; h++) {
#pragma unroll
            for (int i = 0; i < 8; i++) o[i] = lds32(ka + vo + (8 * h + i) * 64);
#pragma unroll
            for (int i = 0; i < 8; i++) o[i] = bmul2(bfma2(kk[8 * h + i + 3], w0, bfma2(kk[8 * h + i + 2], w1, bfma2(kk[8 * h + i + 1], w2, bmul2(kk[8 * h + i], w3)))), o[i]);
            if (h == 0) {
#pragma unroll
              for (int i = 11; i < 19; i++) kk[i] = lds32(ka + i * 64);
            }
            __syncwarp();
            sts128(ka + so + h * 512, __byte_perm(o[1], o[0], 0x5410), __byte_perm(o[3], o[2], 0x5410), __byte_perm(o[5], o[4], 0x5410), __byte_perm(o[7], o[6], 0x5410));
            sts128(ka + so + h * 512 + 1024, __byte_perm(o[1], o[0], 0x7632), __byte_perm(o[3], o[2], 0x7632), __byte_perm(o[5], o[4], 0x7632), __byte_perm(o[7], o[6], 0x7632));
          }
          asm volatile("fence.proxy.async.shared::cta;" ::: "memory");
          __syncwarp();
          if (lane == 0) {
            const int blk = (b & 1) * 10 + 2 * pg + hw;
            asm volatile("cp.async.bulk.tensor.5d.global.shared::cta.bulk_group [%0, {%2,%3,%3,%3,%4}], [%1];" ::"l"(&maps.xs), "r"(ka + vo), "r"(rc * 16), "r"(0), "r"((blk / 5) * 160 + blk % 5) : "memory");
          }
          ka += 8576;
        }
        if (lane == 0) {
          asm volatile("cp.async.bulk.commit_group;" ::: "memory");
          asm volatile("cp.async.bulk.wait_group.read 0;" ::: "memory");
        }
        bar_sync(3, 64);
        if (ht == 0) {
          TS1(12);
          mbar_expect_tx(BAR(B_HR), 20480);
          for (int c = 0; c < 5; c++) bulk_g2s(sb + SM_D + 128 + c * TP + 4128, P.ssm_k + (size_t)(ch0 + 32 * c) * 2048, 4096, BAR(B_HR));
        }
        uint32_t old = 0;
        if (lane == 0) {
          asm volatile("cp.async.bulk.wait_group 0;" ::: "memory");
          mbar_arrive(BAR(B_KD));
          if (hw) {
            TS1(6);
            mbar_wait(BAR(B_KD), 0);
            mbar_wait(BAR(B_GF), 0);
            TS1(20);
            asm volatile("atom.relaxed.gpu.global.add.u32 %0, [%1], 1;" : "=r"(old) : "l"(&g_cnt[0]) : "memory");
          }
        }
        if (lane < 20) sts128(sb + SM_D + 96 + (lane >> 2) * TP + ((lane >> 1) & 1) * 4128 + (lane & 1) * 16, 0, 0, 0, 0);
        uint32_t dv = 0;
        if (ht < 5) dv = __ldg((const unsigned short*)(P.ssm_D + ch0 + 32 * ht));
        mbar_wait(BAR(B_HR), 0);
        if (ht < 5) {
          const uint32_t a0 = sb + SM_D + 128 + 4128 + ht * TP;
          asm volatile("st.shared.u32 [%0], %1;" ::"r"(a0), "r"(badd2(lds32(a0), dv)) : "memory");
        }
        __syncwarp();
        if (ht == 32) TS1(13);
#pragma unroll 1
        for (int c = 0; c < 5; c++) {
          const uint32_t d = sb + SM_D + 128 + c * TP + hw * 2048 + lane * 16;
          uint4 v[4]; uint32_t pv[4];
#pragma unroll
          for (int i = 0; i < 4; i++) { v[i] = lds128(d + 4128 + i * 512); pv[i] = lds32(d + 4124 + i * 512); }
#pragma unroll
          for (int i = 0; i < 4; i++)
            sts128(d + i * 512, __byte_perm(pv[i], v[i].x, 0x5432), __byte_perm(v[i].x, v[i].y, 0x5432), __byte_perm(v[i].y, v[i].z, 0x5432), __byte_perm(v[i].z, v[i].w, 0x5432));
          if (c == 1 && ht == 32) { asm volatile("st.shared.u32 [%0], %1;" ::"r"(sb + SM_BAR + 576), "r"((old & ~127u) + 128u) : "memory"); mbar_arrive(BAR(B_PRE)); TS1(8); }
        }
        __syncwarp();
        if (lane == 0) {
          mbar_arrive(BAR(B_HC));
          if (hw) TS1(14);
          mbar_wait(BAR(B_HS + hw), 0);
          TS1(5 + hw * 10);
          bulk_s2g(g_h + ((size_t)(rt * 2 + hw) * 24 + ct * 3) * 8192, sb + SM_W + (1 + hw) * 24576, 24576);
          bulk_s2g(g_gate + rt * 128 + hw * 64 + ct * 8, sb + SM_GO + hw * 32, 32);
          asm volatile("cp.async.bulk.commit_group;" ::: "memory");
          asm volatile("cp.async.bulk.wait_group.read 0;" ::: "memory");
          mbar_arrive(BAR(B_HF + hw));
          asm volatile("cp.async.bulk.wait_group 0;" ::: "memory");
          flag_add_relaxed(&g_cnt[(1 + rt * 2 + hw) * 32], 16);
          TS1(26 + hw);
        }
        __syncwarp();
      }
      if (tid == 320) {
#pragma unroll 1
        for (int c = 0; c < 5; c++) {
          mbar_wait(BAR(B_ZR + c), 0);
          TS1(c < 4 ? 16 + c : 28);
          const uint32_t ps = sb + (c >= RM ? SM_D + 128 + c * TP : c < 2 ? SM_R2 + c * 57344 : SM_W + 24576), pp = c < 2 ? 28672 : 8192;
          uint8_t* zd = g_z + (size_t)(ch0 + 32 * c) * 4096;
          bulk_s2g(zd, ps, 4096);
          asm volatile("cp.async.bulk.commit_group;" ::: "memory");
          if (c == 1) {
            mbar_expect_tx(BAR(B_Q), 16384);
            for (int i = 0; i < 4; i++) tma3d(sb + SM_D + i * 4096, &maps.q, BAR(B_Q), 0, rb * 64, cb * 5 + i);
          }
          if (c < RM) {
            asm volatile("cp.async.bulk.wait_group 0;" ::: "memory");
#pragma unroll
            for (int i = 1; i < 4; i++)
              asm volatile("cp.reduce.async.bulk.global.shared::cta.bulk_group.add.noftz.bf16 [%0], [%1], %2;" ::"l"(zd + i * 256), "r"(ps + (i >> 1) * pp + (i & 1) * 4096), "r"(4096 - i * 256) : "memory");
            asm volatile("cp.async.bulk.commit_group;" ::: "memory");
          }
          asm volatile("cp.async.bulk.wait_group.read 0;" ::: "memory");
          mbar_arrive(BAR(B_KV + c));
          if (c == 1) TS1(23);
          asm volatile("cp.async.bulk.wait_group 0;" ::: "memory");
          if (c == 0 || c >= 3) flag_add_relaxed(&g_cnt[(c ? 25 + c * 4 + cb : 33 + cb) * 32], 4);
        }
        TS1(30);
      }
      if (tid == 288) {
        mbar_wait(BAR(B_PRE), 0);
        const uint32_t target = lds32v(sb + SM_BAR + 576);
        mbar_wait(BAR(B_KV + 2), 1);
        mbar_expect_tx(BAR(B_Z), 20480);
        mbar_expect_tx(BAR(B_Z + 1), 4096);
        tma3d(sb + SM_D + 16384, &maps.q, BAR(B_Z), 0, rb * 64, cb * 5 + 4);
        flag_wait(&g_cnt[(33 + cb) * 32], target);
        TS1(21);
        tma2d(sb + SM_D + 20480, &maps.z, BAR(B_Z), rb * 64, cb * 160);
        flag_wait(&g_cnt[(37 + cb) * 32], target);
        TS1(22);
        mbar_wait(BAR(B_ZR + 4), 0);
        uint32_t t0 = clk();
#pragma unroll 1
        for (int c = 1; c < 4; c++) {
          if (ZP && c > 1) { t0 += ZP; for (int it = 0; (int)(clk() - t0) < 0 && it < 200; it++) __nanosleep(20); }
          tma2d(sb + SM_W + (c - 1) * 4096, &maps.z, BAR(B_Z), rb * 64, cb * 160 + 32 * c);
        }
        TS1(24);
        flag_wait(&g_cnt[(41 + cb) * 32], target);
        TS1(31);
        tma2d(sb + SM_W + 12288, &maps.z, BAR(B_Z + 1), rb * 64, cb * 160 + 128);
      }
    }
  } else {
    {
      uint32_t tq;
      asm volatile("mov.u32 %0, %%tid.x;" : "=r"(tq));
      const int wi = __shfl_sync(0xffffffffu, tq >> 5, 0);
      if (elect_one()) {
#pragma unroll 1
        for (int gi = wi + 1; gi < 12; gi += 8) {
          const uint32_t cnt = gi < 5 ? 1 : (uint32_t)(0x80808102040908ull >> (8 * (gi - 5))) & 0xff;
#pragma unroll
          for (int j = 0; j < 6; j++) mbar_init(BAR(gi * 6 + j), cnt);
        }
        asm volatile("fence.proxy.async.shared::cta;" ::: "memory");
      }
      __syncwarp();
    }
    bar_sync(0, 384);
    asm volatile("setmaxnreg.inc.sync.aligned.u32 232;");
    const int t128 = tid & 127, w = __shfl_sync(0xffffffffu, t128 >> 5, 0), lane = tid & 31;
    const uint32_t ra0 = sb + SM_D + 128 + (((lane >> 2) & 1) ? 4128 + 2 * (128 * w + (lane >> 2) - 2 * (lane & 3) - 9) : 2 * (128 * w + (lane >> 2) - 2 * (lane & 3) - 8));
    uint32_t A0[16], A1[16], A2[16];
    {
      float ag[96], au[96];
      const uint64_t dA0 = mkdesc(sb + SM_X + wg * 8192, 16, 1024, 1);
      const uint64_t dB0 = mkdesc(sb + SM_W, 4096, 1024, 1);
      const uint32_t xa = sb + SM_X + wg * 8192 + (16 * w + (lane & 15)) * 128 + (((lane >> 4) ^ (lane & 7)) << 4);
      uint4 A[2];
      TS(18);
      mbar_wait(BAR(B_FX + 0), 0);
      TS(19);
      A[0] = ldsm4(xa);
#pragma unroll
      for (int st = 0; st < 28; st++) {
        const int k = st >> 2, kk = st & 3, n = st >> 1, xs = k % 3;
        if (!(st & 1)) mbar_wait(BAR(B_FW + n % 5), (n / 5) & 1);
        if (LSTEP && st > 0 && st % (LSTEP + !LSTEP) == 0) bar_sync(7, 256);
        if (kk == 0) TS(20 + k);
        WG_FENCE();
        wgmma_rs_tb_n192(ag, A[st & 1], dB0 + (n % 5) * 1536 + (st & 1) * 128, st > 0);
        wgmma_rs_tb_n192(au, A[st & 1], dB0 + (n % 5) * 1536 + 768 + (st & 1) * 128, st > 0);
        WG_COMMIT();
        if (kk == 3 && k < 6 && lane == 0) mbar_arrive(BAR(B_EX + xs));
        WG_WAIT(1);
        if (!(st & 1) && st > 0 && lane == 0) mbar_arrive(BAR(B_EW + (n - 1) % 5));
        if (kk < 3) A[(kk + 1) & 1] = ldsm4((xa ^ ((kk + 1) << 5)) + xs * 16384);
        else if (k < 6) { mbar_wait(BAR(B_FX + (k + 1) % 3), ((k + 1) / 3) & 1); A[0] = ldsm4(xa + ((k + 1) % 3) * 16384); }
      }
      TS(1);
#define G1_UNITS(acc, xsl, wsl) { WG_FENCE(); _Pragma("unroll") for (int kk = 0; kk < 4; kk++) { wgmma_ss_tb_n192(acc, dA0 + (xsl) * 1024 + kk * 2, dB0 + (wsl) * 1536 + (kk >> 1) * 768 + (kk & 1) * 128, 1); if (kk == 3 - HOFF) WG_COMMIT(); } WG_COMMIT(); }
#define G1_UNIT(acc, xsl, wsl) { WG_FENCE(); _Pragma("unroll") for (int kk = 0; kk < 4; kk++) wgmma_ss_tb_n192(acc, dA0 + (xsl) * 1024 + kk * 2, dB0 + (wsl) * 1536 + (kk >> 1) * 768 + (kk & 1) * 128, 1); WG_COMMIT(); }
      mbar_wait(BAR(B_FX + 1), 0);
      mbar_wait(BAR(B_FW + 4), 0);
      if (wg) {
        WG_WAIT(0);
        if (lane == 0) mbar_arrive(BAR(B_EW + 3));
        bar_sync(4, 256);
      }
      TS(8);
      G1_UNIT(ag, 1, 4);
      WG_WAIT(1);
      if (lane == 0 && !wg) mbar_arrive(BAR(B_EW + 3));
      mbar_wait(BAR(B_FX + 2), 0);
      mbar_wait(BAR(B_FW + 0), 1);
      TS(6);
      G1_UNIT(ag, 2, 0);
      WG_WAIT(1);
      if (lane == 0) mbar_arrive(BAR(B_EW + 4));
      TS(9);
      mbar_wait(BAR(B_F9), 0);
      mbar_wait(BAR(B_FW + 1), 1);
      TS(16);
      G1_UNITS(ag, 3, 1);
      WG_WAIT(1);
      bar_arrive(4 + wg, 256);
      TS(14);
      if (lane == 0) mbar_arrive(BAR(B_EW + 0));
      WG_WAIT(0);
      if (lane == 0) mbar_arrive(BAR(B_EW + 1));
      TS(2);
      uint32_t sg[48], dep;
#define SIG(lo, hi) dep = sig_range<lo, hi>(ag, sg, zz);
      SIG(0, SG0)
      TS(15);
      mbar_wait(BAR(B_FW + 2) + dep, 1);
      mbar_wait(BAR(B_FW + 3), 1);
      bar_sync(5 + wg, 256);
      TS(17);
      WG_FENCE();
#define U1(xsl, wsl, kk) wgmma_ss_tb_n192(au, dA0 + (xsl) * 1024 + kk * 2, dB0 + ((wsl) * 1536 + (kk >> 1) * 768 + (kk & 1) * 128 + dep), 1);
#define SGC(n) ((SG0 + (n) * SG1) < 48 ? (SG0 + (n) * SG1) : 48)
      U1(1, 2, 0) U1(1, 2, 1) U1(1, 2, 2) SIG(SGC(0), SGC(1))
      U1(1, 2, 3) WG_COMMIT(); SIG(SGC(1), SGC(2))
      U1(2, 3, 0) SIG(SGC(2), SGC(3))
      U1(2, 3, 1) SIG(SGC(3), SGC(4))
      U1(2, 3, 2) SIG(SGC(4), SGC(5))
      U1(2, 3, 3) WG_COMMIT(); SIG(SGC(5), 48)
      WG_WAIT(1);
      if (lane == 0) mbar_arrive(BAR(B_EW + 2));
      TS(10);
      mbar_wait(BAR(B_FW + 4) + dep, 1);
      TS(12);
      G1_UNITS(au, 3, 4);
      mbar_wait(BAR(B_HC), 0);
      conv_ldA<0, 0>(A0, ra0 + wg * TP, zz); conv_ldA<128, 0>(A1, ra0 + wg * TP, zz);
      WG_WAIT(1);
      if (!wg) bar_arrive(6, 256);
      TS(3);
      mbar_wait(BAR(B_EW + 1 + wg), 1);
      WG_WAIT(0);
      if (lane == 0) mbar_arrive(BAR(B_G1));
      TS(4);
      const uint32_t hb = sb + SM_W + (1 + wg) * 24576 + (16 * w + (lane & 15)) * 128;
#pragma unroll
      for (int j = 0; j < 24; j += 2) {
        uint32_t p[4];
#pragma unroll
        for (int e = 0; e < 4; e++) p[e] = bmul2(sg[2 * j + e], pack_bf16(au[4 * j + 2 * e], au[4 * j + 2 * e + 1]));
        const int cc = (j & 7) + (lane >> 4);
        stsm4(hb + (j >> 3) * 8192 + ((cc ^ (lane & 7)) << 4), p[0], p[1], p[2], p[3]);
      }
      asm volatile("fence.proxy.async.shared::cta;" ::: "memory");
      mbar_arrive(BAR(B_HS + wg));
      TS(5);
    }
      uint32_t pb = sb + SM_R2 + wg * 57344, pitch = 28672;
      const uint32_t po = (w & 1) * 4096 + (lane >> 4) * 256 + (lane & 4) * 32 + (((lane >> 1) ^ lane) & 4) * 16 + (lane & 3) * 16;
      mbar_wait(BAR(B_XI), 0);
      conv_dupA(A0, zz); conv_dupA(A1, zz);
#pragma unroll 1
      for (int c = wg; c < 4; c += 2) {
        const uint32_t ra = ra0 + c * TP;
        const uint64_t dX = mkdesc(sb + SM_W + c * XCH + 256, XP, 128, 0);
        float T0[64], T1[16], T2[32], T3[16];
        TS(27 + (c >> 1));
        WG_FENCE();
#pragma unroll
        for (int s = 0; s < 8; s++) {
          wgmma_rs<128>(T0, (s < 4 ? A0 : A1 - 16) + 4 * s, dX - s, s > 0);
          if (s == 3 || s == 7) WG_COMMIT();
        }
        if (c >= 2) { pb = sb + SM_W + (1 + wg) * 24576; pitch = 8192; }
        conv_ldA<3072>(A2, ra, zz);
        conv_grp<32, 0>(T3, A2, dX);
        WG_WAIT(2); conv_ldA<3072 + 128>(A0, ra, zz);
        conv_grp<32, 1>(T3, A0, dX);
        WG_WAIT(2); conv_ldA<1024>(A1, ra, zz);
        conv_grp2<0>(T2, T1, A1, dX);
        WG_WAIT(2); conv_ldA<1024 + 128>(A2, ra, zz);
        conv_grp2<1>(T2, T1, A2, dX);
        WG_WAIT(2); conv_ldA<2048>(A0, ra, zz);
        conv_grp<64, 0, 1>(T2, A0, dX);
#pragma unroll
        for (int i = 0; i < 16; i++) fadd_v(T0[48 + i], T3[i]);
        WG_WAIT(2); conv_ldA<2048 + 128>(A1, ra, zz);
        conv_grp<64, 1>(T2, A1, dX);
        WG_WAIT(2);
#pragma unroll
        for (int i = 0; i < 16; i++) fadd_v(T0[16 + i], T1[i]);
        const uint32_t rn = c < 2 ? ra + 2 * TP : ra0 + 4 * TP + (wg ? 0 : 1024);
        WG_WAIT(1); conv_ldA<0>(A0, rn, zz);
        mbar_wait(BAR(c < 2 ? B_G1 : B_HF + wg), 0);
        const uint32_t pa = pb + po + (w >> 1) * pitch;
#pragma unroll
        for (int j = 0; j < 8; j += 2)
          stsm4t(pa + j * 256, pack_bf16(T0[4 * j], T0[4 * j + 1]), pack_bf16(T0[4 * j + 2], T0[4 * j + 3]), pack_bf16(T0[4 * j + 4], T0[4 * j + 5]), pack_bf16(T0[4 * j + 6], T0[4 * j + 7]));
        WG_WAIT(0); conv_ldA<128>(A1, rn, zz);
        TS(30 + (c >> 1));
#pragma unroll
        for (int i = 0; i < 32; i++) T0[32 + i] += T2[i];
#pragma unroll
        for (int j = 8; j < 16; j += 2)
          stsm4t(pa + j * 256, pack_bf16(T0[4 * j], T0[4 * j + 1]), pack_bf16(T0[4 * j + 2], T0[4 * j + 3]), pack_bf16(T0[4 * j + 4], T0[4 * j + 5]), pack_bf16(T0[4 * j + 6], T0[4 * j + 7]));
        if (c < RM) red_fin(BAR(B_ZR + c));
      }
      const uint32_t ra = ra0 + 4 * TP;
      const uint64_t dX = mkdesc(sb + SM_W + 4 * XCH + 256, XP, 128, 0);
      uint4 v[2][4];
      TS(29);
#define PST(pa, T, j) stsm4t(pa, pack_bf16(T[4 * (j)], T[4 * (j) + 1]), pack_bf16(T[4 * (j) + 2], T[4 * (j) + 3]), pack_bf16(T[4 * (j) + 4], T[4 * (j) + 5]), pack_bf16(T[4 * (j) + 6], T[4 * (j) + 7]))
    const int g = lane >> 2;
    const int frow = 16 * w + (lane & 7) + 8 * ((lane >> 3) & 1);
    const uint32_t fo = frow * 64 + (((lane >> 4) ^ ((frow >> 1) & 3)) << 4);

    if (wg == 0) {
      float acc[80];
      const uint64_t dA0 = mkdesc(sb, 16, 1024, 1), dB0 = mkdesc(sb, 4096, 512, 2);
      {
        float T1[16], T2[32];
        WG_FENCE();
#pragma unroll
        for (int s = 0; s < 8; s++) {
          wgmma_rs<64>(T2, (s < 4 ? A0 : A1 - 16) + 4 * s, dX + 32 - s, s > 0);
          wgmma_rs<32>(T1, (s < 4 ? A0 : A1 - 16) + 4 * s, dX - s, s > 0);
          if (s == 3 || s == 7) WG_COMMIT();
          if (RM <= 2) {
            if (s == RQ0) { bar_sync(1, 128); red_ld(v, sb + SM_W + 24576, t128); }
            if (s == RQ1) red_st(v, sb + SM_D + 128 + 2 * TP, t128);
            if (s == RQ2) { red_fin(BAR(B_ZR + 2)); TS(34); }
          }
        }
        conv_ldA<2048>(A2, ra, zz);
        conv_grp<64, 0, 1>(T2, A2, dX);
        WG_WAIT(2); conv_ldA<2048 + 128>(A0, ra, zz);
        conv_grp<64, 1>(T2, A0, dX);
        bar_sync(8, 256);
        const uint32_t pa = sb + SM_W + po + (w >> 1) * 8192 + 1024;
        WG_WAIT(2);
        PST(pa, T1, 0); PST(pa + 512, T1, 2);
        mbar_wait(BAR(B_F2), 0);
        WG_FENCE();
#pragma unroll
        for (int kk = 0; kk < 4; kk++) wgmma_ss_tb_n160(acc, dA0 + (g2a(0) / 16 + kk * 2), dB0 + (g2b(0) / 16 + kk * 64), kk > 0);
        WG_COMMIT();
        WG_WAIT(1);
        TS(32);
#pragma unroll
        for (int j = 0; j < 8; j += 2) PST(pa + 1024 + j * 256, T2, j);
        bar_arrive(7, 256);
        TS(7);
      }
#pragma unroll
      for (int c = EG; c < 24; c++) {
        mbar_wait(BAR(B_F2 + g2s(c)), g2u(c) & 1);
        if (c & 1) TS(36 + (c >> 1));
        WG_FENCE();
#pragma unroll
        for (int kk = 0; kk < 4; kk++) {
          wgmma_ss_tb_n160(acc, dA0 + (g2a(g2s(c)) / 16 + kk * 2), dB0 + (g2b(g2s(c)) / 16 + kk * 64), c > 0 || kk > 0);
          if (kk == PSP || kk == 3) WG_COMMIT();
          if (kk == PSP && c > 0 && c < 22) { WG_WAIT(1); if (lane == 0) mbar_arrive(BAR(B_E2 + g2s(c - 1))); }
        }
      }
      constexpr int OS = g2s(20) < 4 ? 20 : g2s(19) < 4 ? 19 : 18;
      const uint32_t og = sb + g2a(g2s(OS)) + frow * 336 + ((lane >> 4) << 4);
      mbar_wait(BAR(B_E2 + g2s(OS)), g2u(OS) & 1);
      TS(11);
      mbar_wait(BAR(B_GA), 0);
      uint4 ga[10];
#pragma unroll
      for (int j = 0; j < 10; j++) ga[j] = ldsm4(sb + SM_D + (j >> 1) * 4096 + (fo ^ ((j & 1) << 5)));
      const float gv0 = __uint_as_float(lds32(sb + SM_GT + (16 * w + g) * 4)), gv1 = __uint_as_float(lds32(sb + SM_GT + (16 * w + g + 8) * 4));
      const uint32_t om0 = pack_bf16(1.0f - gv0, 1.0f - gv0), om1 = pack_bf16(1.0f - gv1, 1.0f - gv1);
      WG_WAIT(0);
      TS(12);
#pragma unroll
      for (int j = 0; j < 10; j++) {
        const uint32_t o0 = badd2(ga[j].x, bmul2(om0, pack_bf16(acc[8 * j + 0], acc[8 * j + 1])));
        const uint32_t o1 = badd2(ga[j].y, bmul2(om1, pack_bf16(acc[8 * j + 2], acc[8 * j + 3])));
        const uint32_t o2 = badd2(ga[j].z, bmul2(om0, pack_bf16(acc[8 * j + 4], acc[8 * j + 5])));
        const uint32_t o3 = badd2(ga[j].w, bmul2(om1, pack_bf16(acc[8 * j + 6], acc[8 * j + 7])));
        stsm4(og + j * 32, o0, o1, o2, o3);
      }
      TS(28);
      __syncwarp();
      {
        const uint32_t so = sb + g2a(g2s(OS)) + w * (16 * 336) + lane * 16;
        uint8_t* go = P.out + (size_t)(rb * 64 + w * 16) * 1280 + cb * 320 + lane * 16;
        uint4 ov[10];
#pragma unroll
        for (int i = 0; i < 10; i++) ov[i] = lds128m(so + i * 512 + (((i * 32 + lane) * 3277) >> 16) * 16);
        TS(35);
#pragma unroll
        for (int i = 0; i < 10; i++) *(uint4*)(go + i * 512 + (((i * 32 + lane) * 3277) >> 16) * 960) = ov[i];
      }
      TS(13);
    } else {
      {
        float T0[64], T3[16];
        bar_arrive(8, 256);
        WG_FENCE();
#pragma unroll
        for (int s = 0; s < 8; s++) {
          wgmma_rs<128>(T0, (s < 4 ? A0 : A1 - 16) + 4 * s, dX - s, s > 0);
          if (s == 3 || s == 7) WG_COMMIT();
          if (s == RP0) { bar_sync(2, 128); red_ld(v, sb + SM_W + 49152, t128); }
          if (s == RP1) red_st(v, sb + SM_D + 128 + 3 * TP, t128);
          if (s == RP2) { red_fin(BAR(B_ZR + 3)); TS(34); }
        }
        conv_ldA<3072>(A2, ra, zz);
        conv_grp<32, 0>(T3, A2, dX);
        WG_WAIT(2); conv_ldA<3072 + 128>(A0, ra, zz);
        conv_grp<32, 1>(T3, A0, dX);
        const uint32_t pa = sb + SM_W + po + (w >> 1) * 8192;
        bar_sync(7, 256);
        uint4 u[6];
#pragma unroll
        for (int j = 0; j < 6; j++) u[j] = ldsm4t(pa + 1024 + j * 512);
        WG_WAIT(2);
        PST(pa, T0, 0); PST(pa + 512, T0, 2);
#define PSTA(j) stsm4t(pa + (j) * 256, badd2(u[(j) / 2 - 2].x, pack_bf16(T0[4 * (j)], T0[4 * (j) + 1])), badd2(u[(j) / 2 - 2].y, pack_bf16(T0[4 * (j) + 2], T0[4 * (j) + 3])), \
                       badd2(u[(j) / 2 - 2].z, pack_bf16(T0[4 * (j) + 4], T0[4 * (j) + 5])), badd2(u[(j) / 2 - 2].w, pack_bf16(T0[4 * (j) + 6], T0[4 * (j) + 7])))
#pragma unroll
        for (int j = 4; j < 12; j += 2) PSTA(j);
        WG_WAIT(0);
        TS(32);
#pragma unroll
        for (int i = 0; i < 16; i++) T0[48 + i] += T3[i];
        PSTA(12); PSTA(14);
        TS(7);
        bar_sync(2, 128);
        TS(1);
        red_ld(v, sb + SM_W, t128);
        red_st(v, sb + SM_D + 128 + 4 * TP, t128);
        TS(2);
        red_fin(BAR(B_ZR + 4));
      }
      TS(35);
      const uint32_t zo = sb + ((lane & 7) + 8 * (lane >> 4)) * 128 + (((w + ((((lane >> 3) ^ rb) & 1) << 2)) ^ (lane & 7)) << 4);
      mbar_wait(BAR(B_Q), 0);
      mbar_wait(BAR(B_Z), 0);
      TS(10);
      uint4 zr[10], qr[10];
#pragma unroll
      for (int j = 0; j < 10; j++) { if (j < 8) zr[j] = ldsm4t(zo + (j < 2 ? SM_D + 20480 : SM_W - 4096) + j * 2048); qr[j] = ldsm4(sb + SM_D + (j >> 1) * 4096 + (fo ^ ((j & 1) << 5))); }
      const float gv0 = __uint_as_float(lds32(sb + SM_GT + (16 * w + g) * 4)), gv1 = __uint_as_float(lds32(sb + SM_GT + (16 * w + g + 8) * 4));
      const uint32_t g0 = pack_bf16(gv0, gv0), g1 = pack_bf16(gv1, gv1);
#pragma unroll
      for (int j = 0; j < 10; j++) {
        if (j == 8) { mbar_wait(BAR(B_Z + 1), 0); TS(11); zr[8] = ldsm4t(zo + SM_W + 6 * 2048); zr[9] = ldsm4t(zo + SM_W + 7 * 2048); }
        stsm4(sb + SM_D + (j >> 1) * 4096 + (fo ^ ((j & 1) << 5)), bmul2(g0, bmul2(qr[j].x, zr[j].x)), bmul2(g1, bmul2(qr[j].y, zr[j].y)), bmul2(g0, bmul2(qr[j].z, zr[j].z)), bmul2(g1, bmul2(qr[j].w, zr[j].w)));
      }
      mbar_arrive(BAR(B_GA));
      TS(13);
    }
  }
}

typedef CUresult (*EncFn)(CUtensorMap*, CUtensorMapDataType, cuuint32_t, void*, const cuuint64_t*, const cuuint64_t*, const cuuint32_t*, const cuuint32_t*,
                          CUtensorMapInterleave, CUtensorMapSwizzle, CUtensorMapL2promotion, CUtensorMapFloatOOBfill);

void enc(EncFn fn, CUtensorMap* m, CUtensorMapDataType dt, int rank, const void* p, const cuuint64_t* gd, const cuuint64_t* gs, const cuuint32_t* bd, CUtensorMapSwizzle sw) {
  cuuint32_t es[5] = {1, 1, 1, 1, 1};
  fn(m, dt, rank, (void*)p, gd, gs, bd, es, CU_TENSOR_MAP_INTERLEAVE_NONE, sw, CU_TENSOR_MAP_L2_PROMOTION_L2_128B, CU_TENSOR_MAP_FLOAT_OOB_FILL_NONE);
}

}

extern "C" void kernel_launch(void* const* d_in, const int* in_sizes, int n_in, void* d_out, int out_size) {
  static EncFn fn = nullptr;
  static void *zp = nullptr, *xp = nullptr;
  if (!fn) {
    cudaGetSymbolAddress(&zp, g_z);
    cudaGetSymbolAddress(&xp, g_X);
    void* f = nullptr; cudaDriverEntryPointQueryResult qr;
    cudaGetDriverEntryPoint("cuTensorMapEncodeTiled", &f, cudaEnableDefault, &qr);
    fn = (EncFn)f;
    cudaFuncSetAttribute(fused_kernel, cudaFuncAttributeMaxDynamicSharedMemorySize, SM_TOTAL);
  }
  Maps m;
  const CUtensorMapDataType BF = CU_TENSOR_MAP_DATA_TYPE_BFLOAT16;
  { cuuint64_t gd[2] = {640, 2048}, gs[1] = {1280}; cuuint32_t bd[2] = {64, 128}; enc(fn, &m.x, BF, 2, d_in[0], gd, gs, bd, CU_TENSOR_MAP_SWIZZLE_128B); }
  { cuuint64_t gd[3] = {64, 640, 24}, gs[2] = {3072, 128}; cuuint32_t bd[3] = {64, 32, 3};
    enc(fn, &m.wg, BF, 3, d_in[7], gd, gs, bd, CU_TENSOR_MAP_SWIZZLE_128B); enc(fn, &m.wu, BF, 3, d_in[8], gd, gs, bd, CU_TENSOR_MAP_SWIZZLE_128B); }
  { cuuint64_t gd[3] = {32, 1536, 20}, gs[2] = {1280, 64}; cuuint32_t bd[3] = {32, 64, 4}; enc(fn, &m.wd, BF, 3, d_in[9], gd, gs, bd, CU_TENSOR_MAP_SWIZZLE_64B); }
  { cuuint64_t gd[3] = {32, 2048, 20}, gs[2] = {1280, 64}; cuuint32_t bk[3] = {32, 35, 2}, bv[3] = {32, 32, 2};
    enc(fn, &m.k, BF, 3, d_in[1], gd, gs, bk, CU_TENSOR_MAP_SWIZZLE_NONE); enc(fn, &m.v, BF, 3, d_in[2], gd, gs, bv, CU_TENSOR_MAP_SWIZZLE_NONE); }
  { cuuint64_t gd[5] = {1024, 16, 2, 2, 485}, gs[4] = {40960, 2048, 20480, 4096}; cuuint32_t bd[5] = {16, 16, 2, 2, 1}; enc(fn, &m.xs, BF, 5, xp, gd, gs, bd, CU_TENSOR_MAP_SWIZZLE_NONE); }
  { cuuint64_t gd[3] = {64, 16, 1280}, gs[2] = {128, 2048}; cuuint32_t bd[3] = {64, 18, 10}; enc(fn, &m.xl, BF, 3, xp, gd, gs, bd, CU_TENSOR_MAP_SWIZZLE_NONE); }
  { cuuint64_t gd[3] = {32, 2048, 20}, gs[2] = {1280, 64}; cuuint32_t bd[3] = {32, 64, 5}, bq[3] = {32, 64, 1};
    enc(fn, &m.q, BF, 3, d_in[0], gd, gs, bq, CU_TENSOR_MAP_SWIZZLE_64B); enc(fn, &m.o, BF, 3, d_out, gd, gs, bd, CU_TENSOR_MAP_SWIZZLE_64B); }
  { cuuint64_t gd[2] = {2048, 640}, gs[1] = {4096}; cuuint32_t bd[2] = {64, 32}; enc(fn, &m.z, BF, 2, zp, gd, gs, bd, CU_TENSOR_MAP_SWIZZLE_128B); }
  Ptrs p;
  p.out = (uint8_t*)d_out; p.x = (const __nv_bfloat16*)d_in[0]; p.shift_k = (const __nv_bfloat16*)d_in[3]; p.ssm_k = (const __nv_bfloat16*)d_in[4];
  p.ssm_D = (const __nv_bfloat16*)d_in[5]; p.gate_w = (const __nv_bfloat16*)d_in[10];
  p.wg = (const __nv_bfloat16*)d_in[7]; p.wu = (const __nv_bfloat16*)d_in[8];
  fused_kernel<<<128, 384, SM_TOTAL, cudaStreamPerThread>>>(m, p, 0u);
}
```

```cpp
#include <cuda_runtime.h>
#include <cuda_bf16.h>
#include <cuda.h>
#include <stdint.h>

namespace {

constexpr int XP = 2304;
constexpr int XCH = 2 * XP;
constexpr int TP = 8320;
#define KV0 3
#define KV1 4
#define KV2 5
#define KV3 6
#define KV4 7
#define NPRE 1
#define PD 10
#define PF0 10
#define LSTEP 0
#define WD_N 99
#define SK_N 9
#define MAP1 1
#define MAP2 1
#define SGB 8
#define HOFF 2
#define PF_N 14
#define X9_N 15
#define WK 6
#define SG0 40
#define QC 1
#define G2P 2
#define RP0 1
#define RP1 4
#define RP2 7
#define RQ0 1
#define RQ1 3
#define RQ2 6
#define SG1 4

#define RM 2
#define PER 320
#define TICK 1
#define TDEL 100
#define XS 7
#define XFIX 0
#define RS 5
#define EG 1
#define NOZ 0
#define ZP 0
#define DS 0
#define WU 4
#define WP 2
#define LS 4
#define E1 2
#define NB1 2
#define GN 4
#define GC (19 - 8 / GN)
#define NA 64
#define MMA_A wgmma_ss_tb_n64
#define MMA_B wgmma_ss_tb_n96
#define WL_N 17
#define GL 1
#define SW 26
#define PF8 17
#define PW 1
#define SHB 1
#define ROLL2 1
#define SPN 0
#define FAKE 0
#define PSP 3
__host__ __device__ constexpr int g2s(int c) { return c < XS ? c % 5 : (c - XS) % 6 == 0 ? 5 : (XS + (c - XS) % 6 - 1) % 5; }
__host__ __device__ constexpr int g2u(int c) { return c < XS ? c / 5 : (c - XS) / 6 + (g2s(c) < 5 ? (XS - g2s(c) + 4) / 5 : 0); }
constexpr uint32_t SM_W = 0;
constexpr uint32_t SM_X = 122880;
constexpr uint32_t SM_R2 = 73728;
constexpr uint32_t SM_D = 188416;
__host__ __device__ constexpr uint32_t g2a(int s) { return s < 4 ? SM_R2 + s * 28672 : s == 4 ? 65536 : SM_D + 24576; }
__host__ __device__ constexpr uint32_t g2b(int s) { return s < 4 ? SM_R2 + s * 28672 + 8192 : s == 4 ? 24576 : 45056; }
constexpr uint32_t SM_BAR = 231296;
constexpr uint32_t SM_GAP = 172032;
constexpr uint32_t SM_GT = SM_BAR + 592;
constexpr uint32_t SM_GO = SM_GT + 256;
constexpr uint32_t SM_TOTAL = SM_GO + 64;
enum { B_FX = 0  , B_FW = 3  , B_KV = 8  , B_F2 = 13  , B_WD = 27, B_XI = 19, B_HR = 20, B_HF = 21  , B_Z = 28  , B_WP = 23, B_F9 = 24, B_GF = 25, B_PRE = 26,
       B_EW = 30  , B_EX = 36  , B_G1 = 39, B_E2 = 42  , B_HC = 48, B_Q = 49, B_KD = 50, B_HS = 54  , B_ZR = 60  , B_GA = 65, B_PF = 66   };

__device__ __align__(1024) uint8_t g_X[640 * 4096];
__device__ __align__(1024) uint8_t g_h[2048 * 1536 * 2];
__device__ __align__(1024) uint8_t g_wd[1536 * 640 * 2];
__device__ __align__(1024) uint8_t g_z[640 * 4096];
__device__ __align__(1024) float g_gate[2048];
__device__ uint32_t g_cnt[46 * 32];
#define TS(i)
#define TS1(i)
#define TR(v)
#define TW(i, v)

struct Maps { CUtensorMap x, wg, wu, wd, k, v, q, o, z, xs, xl; };
struct Ptrs { uint8_t* out; const __nv_bfloat16 *x, *shift_k, *ssm_k, *ssm_D, *gate_w, *wg, *wu; };

__device__ __forceinline__ uint32_t clk() { uint32_t t; asm volatile("mov.u32 %0, %%clock;" : "=r"(t) :: "memory"); return t; }
__device__ __forceinline__ uint32_t smem_u32(const void* p) { return (uint32_t)__cvta_generic_to_shared(p); }
__device__ __forceinline__ bool elect_one() { uint32_t p; asm volatile("{.reg .pred P; elect.sync _|P, 0xffffffff; selp.u32 %0, 1, 0, P;}" : "=r"(p)); return p; }
__device__ __forceinline__ void mbar_init(uint32_t bar, uint32_t cnt) { asm volatile("mbarrier.init.shared::cta.b64 [%0], %1;" ::"r"(bar), "r"(cnt)); }
__device__ __forceinline__ void mbar_expect_tx(uint32_t bar, uint32_t bytes) { asm volatile("mbarrier.arrive.expect_tx.shared::cta.b64 _, [%0], %1;" ::"r"(bar), "r"(bytes) : "memory"); }
__device__ __forceinline__ void mbar_arrive(uint32_t bar) { asm volatile("mbarrier.arrive.shared::cta.b64 _, [%0];" ::"r"(bar) : "memory"); }
__device__ __forceinline__ void mbar_wait(uint32_t bar, uint32_t parity) {
  uint32_t ok;
  asm volatile("{.reg .pred p; mbarrier.try_wait.parity.shared::cta.b64 p, [%1], %2; selp.u32 %0,1,0,p;}" : "=r"(ok) : "r"(bar), "r"(parity) : "memory");
  if (!ok) {
    uint32_t it = 0;
    do {
      asm volatile("{.reg .pred p; mbarrier.try_wait.parity.shared::cta.b64 p, [%1], %2, 2000; selp.u32 %0,1,0,p;}" : "=r"(ok) : "r"(bar), "r"(parity) : "memory");
    } while (!ok && ++it < 100000u);
  }
}
__device__ __forceinline__ void mbar_spin(uint32_t bar, uint32_t parity) {
  uint32_t ok, it = 0;
  do {
    asm volatile("{.reg .pred p; mbarrier.try_wait.parity.shared::cta.b64 p, [%1], %2; selp.u32 %0,1,0,p;}" : "=r"(ok) : "r"(bar), "r"(parity) : "memory");
  } while (!ok && ++it < 4000000u);
}
__device__ __forceinline__ void flag_wait(const uint32_t* p, uint32_t target) {
  uint32_t v, it = 0;
  while (true) {
    asm volatile("ld.acquire.gpu.global.u32 %0, [%1];" : "=r"(v) : "l"(p) : "memory");
    if ((int)(v - target) >= 0) break;
    if (++it > 400000u) break;
    __nanosleep(20);
  }
  asm volatile("fence.proxy.async.global;" ::: "memory");
}
__device__ __forceinline__ void flag_add(uint32_t* p, uint32_t v) {
  asm volatile("red.release.gpu.global.add.u32 [%0], %1;" ::"l"(p), "r"(v) : "memory");
}
__device__ __forceinline__ void flag_add_relaxed(uint32_t* p, uint32_t v) {
  asm volatile("red.relaxed.gpu.global.add.u32 [%0], %1;" ::"l"(p), "r"(v) : "memory");
}
__device__ __forceinline__ bool mbar_test(uint32_t bar, uint32_t parity) {
  uint32_t ok;
  asm volatile("{.reg .pred p; mbarrier.test_wait.parity.shared::cta.b64 p, [%1], %2; selp.u32 %0,1,0,p;}" : "=r"(ok) : "r"(bar), "r"(parity) : "memory");
  return ok;
}
__device__ __forceinline__ void cp_async16(uint32_t dst, const void* src) { asm volatile("cp.async.cg.shared.global [%0], [%1], 16;" ::"r"(dst), "l"(src) : "memory"); }
__device__ __forceinline__ void tma2d(uint32_t dst, const CUtensorMap* m, uint32_t bar, int c0, int c1) {
  asm volatile("cp.async.bulk.tensor.2d.shared::cluster.global.mbarrier::complete_tx::bytes [%0], [%1, {%3,%4}], [%2];" ::"r"(dst), "l"(m), "r"(bar), "r"(c0), "r"(c1) : "memory");
}
__device__ __forceinline__ void tma3d(uint32_t dst, const CUtensorMap* m, uint32_t bar, int c0, int c1, int c2) {
  asm volatile("cp.async.bulk.tensor.3d.shared::cluster.global.mbarrier::complete_tx::bytes [%0], [%1, {%3,%4,%5}], [%2];" ::"r"(dst), "l"(m), "r"(bar), "r"(c0), "r"(c1), "r"(c2) : "memory");
}
__device__ __forceinline__ void tma3d_store(const CUtensorMap* m, uint32_t src, int c0, int c1, int c2) {
  asm volatile("cp.async.bulk.tensor.3d.global.shared::cta.bulk_group [%0, {%2,%3,%4}], [%1];" ::"l"(m), "r"(src), "r"(c0), "r"(c1), "r"(c2) : "memory");
}
__device__ __forceinline__ void bulk_g2s(uint32_t dst, const void* src, uint32_t bytes, uint32_t bar) {
  asm volatile("cp.async.bulk.shared::cluster.global.mbarrier::complete_tx::bytes [%0], [%1], %2, [%3];" ::"r"(dst), "l"(src), "r"(bytes), "r"(bar) : "memory");
}
__device__ __forceinline__ void bulk_s2g(void* dst, uint32_t src, uint32_t bytes) {
  asm volatile("cp.async.bulk.global.shared::cta.bulk_group [%0], [%1], %2;" ::"l"(dst), "r"(src), "r"(bytes) : "memory");
}
__device__ __forceinline__ void l2_prefetch(const void* src, uint32_t bytes) {
  asm volatile("cp.async.bulk.prefetch.L2.global [%0], %1;" ::"l"(src), "r"(bytes) : "memory");
}
__device__ __forceinline__ void tma3d_prefetch(const CUtensorMap* m, int c0, int c1, int c2) {
  asm volatile("cp.async.bulk.prefetch.tensor.3d.L2.global.tile [%0, {%1,%2,%3}];" ::"l"(m), "r"(c0), "r"(c1), "r"(c2) : "memory");
}
__device__ __forceinline__ void tmap_prefetch(const CUtensorMap* m) { asm volatile("prefetch.tensormap [%0];" ::"l"(m) : "memory"); }
__device__ __forceinline__ uint64_t mkdesc(uint32_t addr, uint32_t lbo, uint32_t sbo, uint32_t swz) {
  return (uint64_t)((addr & 0x3FFFF) >> 4) | ((uint64_t)(lbo >> 4) << 16) | ((uint64_t)(sbo >> 4) << 32) | ((uint64_t)swz << 62);
}
#define WG_FENCE() asm volatile("wgmma.fence.sync.aligned;" ::: "memory")
#define WG_COMMIT() asm volatile("wgmma.commit_group.sync.aligned;" ::: "memory")
#define WG_WAIT(n) asm volatile("wgmma.wait_group.sync.aligned " #n ";" ::: "memory")
__device__ __forceinline__ void bar_sync(int id, int n) { asm volatile("bar.sync %0, %1;" ::"r"(id), "r"(n) : "memory"); }
__device__ __forceinline__ void bar_arrive(int id, int n) { asm volatile("bar.arrive %0, %1;" ::"r"(id), "r"(n) : "memory"); }
__device__ __forceinline__ uint32_t pack_bf16(float lo, float hi) { uint32_t r; asm("cvt.rn.bf16x2.f32 %0, %1, %2;" : "=r"(r) : "f"(hi), "f"(lo)); return r; }
__device__ __forceinline__ uint32_t bmul2(uint32_t a, uint32_t b) { uint32_t r; asm("mul.rn.bf16x2 %0, %1, %2;" : "=r"(r) : "r"(a), "r"(b)); return r; }
__device__ __forceinline__ uint32_t badd2(uint32_t a, uint32_t b) { uint32_t r; asm("add.rn.bf16x2 %0, %1, %2;" : "=r"(r) : "r"(a), "r"(b)); return r; }
__device__ __forceinline__ uint32_t bfma2(uint32_t a, uint32_t b, uint32_t c) { uint32_t r; asm("fma.rn.bf16x2 %0, %1, %2, %3;" : "=r"(r) : "r"(a), "r"(b), "r"(c)); return r; }
__device__ __forceinline__ uint32_t lds32(uint32_t a) { uint32_t r; asm volatile("ld.shared.u32 %0, [%1];" : "=r"(r) : "r"(a)); return r; }
__device__ __forceinline__ uint32_t lds32v(uint32_t a) { uint32_t r; asm volatile("ld.shared.u32 %0, [%1];" : "=r"(r) : "r"(a) : "memory"); return r; }
__device__ __forceinline__ uint4 lds128(uint32_t a) { uint4 v; asm volatile("ld.shared.v4.u32 {%0,%1,%2,%3}, [%4];" : "=r"(v.x), "=r"(v.y), "=r"(v.z), "=r"(v.w) : "r"(a)); return v; }
__device__ __forceinline__ uint4 lds128m(uint32_t a) { uint4 v; asm volatile("ld.shared.v4.u32 {%0,%1,%2,%3}, [%4];" : "=r"(v.x), "=r"(v.y), "=r"(v.z), "=r"(v.w) : "r"(a) : "memory"); return v; }
__device__ __forceinline__ void sts128(uint32_t a, uint32_t x, uint32_t y, uint32_t z, uint32_t w) { asm volatile("st.shared.v4.u32 [%0], {%1,%2,%3,%4};" ::"r"(a), "r"(x), "r"(y), "r"(z), "r"(w) : "memory"); }
__device__ __forceinline__ void stg128(void* a, uint32_t x, uint32_t y, uint32_t z, uint32_t w) { asm volatile("st.global.v4.u32 [%0], {%1,%2,%3,%4};" ::"l"(a), "r"(x), "r"(y), "r"(z), "r"(w) : "memory"); }
__device__ __forceinline__ void stsm4(uint32_t a, uint32_t x, uint32_t y, uint32_t z, uint32_t w) { asm volatile("stmatrix.sync.aligned.m8n8.x4.shared.b16 [%0], {%1,%2,%3,%4};" ::"r"(a), "r"(x), "r"(y), "r"(z), "r"(w) : "memory"); }
__device__ __forceinline__ void stsm4t(uint32_t a, uint32_t x, uint32_t y, uint32_t z, uint32_t w) { asm volatile("stmatrix.sync.aligned.m8n8.x4.trans.shared.b16 [%0], {%1,%2,%3,%4};" ::"r"(a), "r"(x), "r"(y), "r"(z), "r"(w) : "memory"); }
__device__ __forceinline__ uint4 ldsm4(uint32_t a) { uint4 v; asm volatile("ldmatrix.sync.aligned.m8n8.x4.shared.b16 {%0,%1,%2,%3}, [%4];" : "=r"(v.x), "=r"(v.y), "=r"(v.z), "=r"(v.w) : "r"(a) : "memory"); return v; }
__device__ __forceinline__ uint4 ldsm4t(uint32_t a) { uint4 v; asm volatile("ldmatrix.sync.aligned.m8n8.x4.trans.shared.b16 {%0,%1,%2,%3}, [%4];" : "=r"(v.x), "=r"(v.y), "=r"(v.z), "=r"(v.w) : "r"(a) : "memory"); return v; }
__device__ __forceinline__ void tanh_h(float& a) { asm volatile("{.reg .f32 t; mul.f32 t, %0, 0f3F000000; tanh.approx.f32 %0, t;}" : "+f"(a)); }
__device__ __forceinline__ uint32_t sig_fin(float lo, float hi, float h) {
  uint32_t r;
  asm volatile("{.reg .f32 a, b; fma.rn.f32 a, %1, %3, %3; fma.rn.f32 b, %2, %3, %3; cvt.rn.bf16x2.f32 %0, b, a;}" : "=r"(r) : "f"(lo), "f"(hi), "f"(h));
  return r;
}
template <int LO, int HI> __device__ __forceinline__ uint32_t sig_range(float* a, uint32_t* sg, uint32_t zz) {
  uint32_t dep = 0;
#pragma unroll
  for (int b = LO; b < HI; b += SGB) {
    const int e = b + SGB < HI ? b + SGB : HI;
#pragma unroll
    for (int i = 2 * b; i < 2 * e; i++) tanh_h(a[i]);
    const float h = __uint_as_float(0x3f000000u | (__float_as_uint(a[2 * e - 1]) & zz));
#pragma unroll
    for (int i = b; i < e; i++) { sg[i] = sig_fin(a[2 * i], a[2 * i + 1], h); dep |= sg[i]; }
  }
  return dep & zz;
}
__device__ __forceinline__ void fadd_v(float& a, float b) { asm volatile("add.f32 %0, %0, %1;" : "+f"(a) : "f"(b)); }

__device__ __forceinline__ void wgmma_ss_tb_n192(float* d, uint64_t da, uint64_t db, int sc) {
  asm volatile("{.reg .pred p; setp.ne.b32 p, %98, 0;\n"
   "wgmma.mma_async.sync.aligned.m64n192k16.f32.bf16.bf16 {%0,%1,%2,%3,%4,%5,%6,%7,%8,%9,%10,%11,%12,%13,%14,%15,%16,%17,%18,%19,%20,%21,%22,%23,%24,%25,%26,%27,%28,%29,%30,%31,%32,%33,%34,%35,%36,%37,%38,%39,%40,%41,%42,%43,%44,%45,%46,%47,%48,%49,%50,%51,%52,%53,%54,%55,%56,%57,%58,%59,%60,%61,%62,%63,%64,%65,%66,%67,%68,%69,%70,%71,%72,%73,%74,%75,%76,%77,%78,%79,%80,%81,%82,%83,%84,%85,%86,%87,%88,%89,%90,%91,%92,%93,%94,%95}, %96, %97, p, 1, 1, 0, 1;}\n"
   : "+f"(d[0]),"+f"(d[1]),"+f"(d[2]),"+f"(d[3]),"+f"(d[4]),"+f"(d[5]),"+f"(d[6]),"+f"(d[7]),"+f"(d[8]),"+f"(d[9]),"+f"(d[10]),"+f"(d[11]),"+f"(d[12]),"+f"(d[13]),"+f"(d[14]),"+f"(d[15]),"+f"(d[16]),"+f"(d[17]),"+f"(d[18]),"+f"(d[19]),"+f"(d[20]),"+f"(d[21]),"+f"(d[22]),"+f"(d[23]),"+f"(d[24]),"+f"(d[25]),"+f"(d[26]),"+f"(d[27]),"+f"(d[28]),"+f"(d[29]),"+f"(d[30]),"+f"(d[31]),"+f"(d[32]),"+f"(d[33]),"+f"(d[34]),"+f"(d[35]),"+f"(d[36]),"+f"(d[37]),"+f"(d[38]),"+f"(d[39]),"+f"(d[40]),"+f"(d[41]),"+f"(d[42]),"+f"(d[43]),"+f"(d[44]),"+f"(d[45]),"+f"(d[46]),"+f"(d[47]),"+f"(d[48]),"+f"(d[49]),"+f"(d[50]),"+f"(d[51]),"+f"(d[52]),"+f"(d[53]),"+f"(d[54]),"+f"(d[55]),"+f"(d[56]),"+f"(d[57]),"+f"(d[58]),"+f"(d[59]),"+f"(d[60]),"+f"(d[61]),"+f"(d[62]),"+f"(d[63]),"+f"(d[64]),"+f"(d[65]),"+f"(d[66]),"+f"(d[67]),"+f"(d[68]),"+f"(d[69]),"+f"(d[70]),"+f"(d[71]),"+f"(d[72]),"+f"(d[73]),"+f"(d[74]),"+f"(d[75]),"+f"(d[76]),"+f"(d[77]),"+f"(d[78]),"+f"(d[79]),"+f"(d[80]),"+f"(d[81]),"+f"(d[82]),"+f"(d[83]),"+f"(d[84]),"+f"(d[85]),"+f"(d[86]),"+f"(d[87]),"+f"(d[88]),"+f"(d[89]),"+f"(d[90]),"+f"(d[91]),"+f"(d[92]),"+f"(d[93]),"+f"(d[94]),"+f"(d[95]) : "l"(da), "l"(db), "r"(sc));
}
__device__ __forceinline__ void wgmma_ss_tb_n160(float* d, uint64_t da, uint64_t db, int sc) {
  asm volatile("{.reg .pred p; setp.ne.b32 p, %82, 0;\n"
   "wgmma.mma_async.sync.aligned.m64n160k16.f32.bf16.bf16 {%0,%1,%2,%3,%4,%5,%6,%7,%8,%9,%10,%11,%12,%13,%14,%15,%16,%17,%18,%19,%20,%21,%22,%23,%24,%25,%26,%27,%28,%29,%30,%31,%32,%33,%34,%35,%36,%37,%38,%39,%40,%41,%42,%43,%44,%45,%46,%47,%48,%49,%50,%51,%52,%53,%54,%55,%56,%57,%58,%59,%60,%61,%62,%63,%64,%65,%66,%67,%68,%69,%70,%71,%72,%73,%74,%75,%76,%77,%78,%79}, %80, %81, p, 1, 1, 0, 1;}\n"
   : "+f"(d[0]),"+f"(d[1]),"+f"(d[2]),"+f"(d[3]),"+f"(d[4]),"+f"(d[5]),"+f"(d[6]),"+f"(d[7]),"+f"(d[8]),"+f"(d[9]),"+f"(d[10]),"+f"(d[11]),"+f"(d[12]),"+f"(d[13]),"+f"(d[14]),"+f"(d[15]),"+f"(d[16]),"+f"(d[17]),"+f"(d[18]),"+f"(d[19]),"+f"(d[20]),"+f"(d[21]),"+f"(d[22]),"+f"(d[23]),"+f"(d[24]),"+f"(d[25]),"+f"(d[26]),"+f"(d[27]),"+f"(d[28]),"+f"(d[29]),"+f"(d[30]),"+f"(d[31]),"+f"(d[32]),"+f"(d[33]),"+f"(d[34]),"+f"(d[35]),"+f"(d[36]),"+f"(d[37]),"+f"(d[38]),"+f"(d[39]),"+f"(d[40]),"+f"(d[41]),"+f"(d[42]),"+f"(d[43]),"+f"(d[44]),"+f"(d[45]),"+f"(d[46]),"+f"(d[47]),"+f"(d[48]),"+f"(d[49]),"+f"(d[50]),"+f"(d[51]),"+f"(d[52]),"+f"(d[53]),"+f"(d[54]),"+f"(d[55]),"+f"(d[56]),"+f"(d[57]),"+f"(d[58]),"+f"(d[59]),"+f"(d[60]),"+f"(d[61]),"+f"(d[62]),"+f"(d[63]),"+f"(d[64]),"+f"(d[65]),"+f"(d[66]),"+f"(d[67]),"+f"(d[68]),"+f"(d[69]),"+f"(d[70]),"+f"(d[71]),"+f"(d[72]),"+f"(d[73]),"+f"(d[74]),"+f"(d[75]),"+f"(d[76]),"+f"(d[77]),"+f"(d[78]),"+f"(d[79]) : "l"(da), "l"(db), "r"(sc));
}
__device__ __forceinline__ void wgmma_ss_tb_n96(float* d, uint64_t da, uint64_t db, int sc) {
  asm volatile("{.reg .pred p; setp.ne.b32 p, %50, 0;\n"
   "wgmma.mma_async.sync.aligned.m64n96k16.f32.bf16.bf16 {%0,%1,%2,%3,%4,%5,%6,%7,%8,%9,%10,%11,%12,%13,%14,%15,%16,%17,%18,%19,%20,%21,%22,%23,%24,%25,%26,%27,%28,%29,%30,%31,%32,%33,%34,%35,%36,%37,%38,%39,%40,%41,%42,%43,%44,%45,%46,%47}, %48, %49, p, 1, 1, 0, 1;}\n"
   : "+f"(d[0]),"+f"(d[1]),"+f"(d[2]),"+f"(d[3]),"+f"(d[4]),"+f"(d[5]),"+f"(d[6]),"+f"(d[7]),"+f"(d[8]),"+f"(d[9]),"+f"(d[10]),"+f"(d[11]),"+f"(d[12]),"+f"(d[13]),"+f"(d[14]),"+f"(d[15]),"+f"(d[16]),"+f"(d[17]),"+f"(d[18]),"+f"(d[19]),"+f"(d[20]),"+f"(d[21]),"+f"(d[22]),"+f"(d[23]),"+f"(d[24]),"+f"(d[25]),"+f"(d[26]),"+f"(d[27]),"+f"(d[28]),"+f"(d[29]),"+f"(d[30]),"+f"(d[31]),"+f"(d[32]),"+f"(d[33]),"+f"(d[34]),"+f"(d[35]),"+f"(d[36]),"+f"(d[37]),"+f"(d[38]),"+f"(d[39]),"+f"(d[40]),"+f"(d[41]),"+f"(d[42]),"+f"(d[43]),"+f"(d[44]),"+f"(d[45]),"+f"(d[46]),"+f"(d[47]) : "l"(da), "l"(db), "r"(sc));
}
__device__ __forceinline__ void wgmma_ss_tb_n64(float* d, uint64_t da, uint64_t db, int sc) {
  asm volatile("{.reg .pred p; setp.ne.b32 p, %34, 0;\n"
   "wgmma.mma_async.sync.aligned.m64n64k16.f32.bf16.bf16 {%0,%1,%2,%3,%4,%5,%6,%7,%8,%9,%10,%11,%12,%13,%14,%15,%16,%17,%18,%19,%20,%21,%22,%23,%24,%25,%26,%27,%28,%29,%30,%31}, %32, %33, p, 1, 1, 0, 1;}\n"
   : "+f"(d[0]),"+f"(d[1]),"+f"(d[2]),"+f"(d[3]),"+f"(d[4]),"+f"(d[5]),"+f"(d[6]),"+f"(d[7]),"+f"(d[8]),"+f"(d[9]),"+f"(d[10]),"+f"(d[11]),"+f"(d[12]),"+f"(d[13]),"+f"(d[14]),"+f"(d[15]),"+f"(d[16]),"+f"(d[17]),"+f"(d[18]),"+f"(d[19]),"+f"(d[20]),"+f"(d[21]),"+f"(d[22]),"+f"(d[23]),"+f"(d[24]),"+f"(d[25]),"+f"(d[26]),"+f"(d[27]),"+f"(d[28]),"+f"(d[29]),"+f"(d[30]),"+f"(d[31]) : "l"(da), "l"(db), "r"(sc));
}
__device__ __forceinline__ void wgmma_rs_tb_n192(float* d, const uint4& a, uint64_t db, int sc) {
  asm volatile("{.reg .pred p; setp.ne.b32 p, %101, 0;\n"
   "wgmma.mma_async.sync.aligned.m64n192k16.f32.bf16.bf16 {%0,%1,%2,%3,%4,%5,%6,%7,%8,%9,%10,%11,%12,%13,%14,%15,%16,%17,%18,%19,%20,%21,%22,%23,%24,%25,%26,%27,%28,%29,%30,%31,%32,%33,%34,%35,%36,%37,%38,%39,%40,%41,%42,%43,%44,%45,%46,%47,%48,%49,%50,%51,%52,%53,%54,%55,%56,%57,%58,%59,%60,%61,%62,%63,%64,%65,%66,%67,%68,%69,%70,%71,%72,%73,%74,%75,%76,%77,%78,%79,%80,%81,%82,%83,%84,%85,%86,%87,%88,%89,%90,%91,%92,%93,%94,%95}, {%96,%97,%98,%99}, %100, p, 1, 1, 1;}\n"
   : "+f"(d[0]),"+f"(d[1]),"+f"(d[2]),"+f"(d[3]),"+f"(d[4]),"+f"(d[5]),"+f"(d[6]),"+f"(d[7]),"+f"(d[8]),"+f"(d[9]),"+f"(d[10]),"+f"(d[11]),"+f"(d[12]),"+f"(d[13]),"+f"(d[14]),"+f"(d[15]),"+f"(d[16]),"+f"(d[17]),"+f"(d[18]),"+f"(d[19]),"+f"(d[20]),"+f"(d[21]),"+f"(d[22]),"+f"(d[23]),"+f"(d[24]),"+f"(d[25]),"+f"(d[26]),"+f"(d[27]),"+f"(d[28]),"+f"(d[29]),"+f"(d[30]),"+f"(d[31]),"+f"(d[32]),"+f"(d[33]),"+f"(d[34]),"+f"(d[35]),"+f"(d[36]),"+f"(d[37]),"+f"(d[38]),"+f"(d[39]),"+f"(d[40]),"+f"(d[41]),"+f"(d[42]),"+f"(d[43]),"+f"(d[44]),"+f"(d[45]),"+f"(d[46]),"+f"(d[47]),"+f"(d[48]),"+f"(d[49]),"+f"(d[50]),"+f"(d[51]),"+f"(d[52]),"+f"(d[53]),"+f"(d[54]),"+f"(d[55]),"+f"(d[56]),"+f"(d[57]),"+f"(d[58]),"+f"(d[59]),"+f"(d[60]),"+f"(d[61]),"+f"(d[62]),"+f"(d[63]),"+f"(d[64]),"+f"(d[65]),"+f"(d[66]),"+f"(d[67]),"+f"(d[68]),"+f"(d[69]),"+f"(d[70]),"+f"(d[71]),"+f"(d[72]),"+f"(d[73]),"+f"(d[74]),"+f"(d[75]),"+f"(d[76]),"+f"(d[77]),"+f"(d[78]),"+f"(d[79]),"+f"(d[80]),"+f"(d[81]),"+f"(d[82]),"+f"(d[83]),"+f"(d[84]),"+f"(d[85]),"+f"(d[86]),"+f"(d[87]),"+f"(d[88]),"+f"(d[89]),"+f"(d[90]),"+f"(d[91]),"+f"(d[92]),"+f"(d[93]),"+f"(d[94]),"+f"(d[95]) : "r"(a.x), "r"(a.y), "r"(a.z), "r"(a.w), "l"(db), "r"(sc));
}
template<int N> __device__ __forceinline__ void wgmma_rs(float* d, const uint32_t* a, uint64_t db, int sc);
template<> __device__ __forceinline__ void wgmma_rs<128>(float* d, const uint32_t* a, uint64_t db, int sc) {
  asm volatile("{.reg .pred p; setp.ne.b32 p, %69, 0;\n"
   "wgmma.mma_async.sync.aligned.m64n128k16.f32.bf16.bf16 {%0,%1,%2,%3,%4,%5,%6,%7,%8,%9,%10,%11,%12,%13,%14,%15,%16,%17,%18,%19,%20,%21,%22,%23,%24,%25,%26,%27,%28,%29,%30,%31,%32,%33,%34,%35,%36,%37,%38,%39,%40,%41,%42,%43,%44,%45,%46,%47,%48,%49,%50,%51,%52,%53,%54,%55,%56,%57,%58,%59,%60,%61,%62,%63}, {%64,%65,%66,%67}, %68, p, 1, 1, 0;}\n"
   : "+f"(d[0]),"+f"(d[1]),"+f"(d[2]),"+f"(d[3]),"+f"(d[4]),"+f"(d[5]),"+f"(d[6]),"+f"(d[7]),"+f"(d[8]),"+f"(d[9]),"+f"(d[10]),"+f"(d[11]),"+f"(d[12]),"+f"(d[13]),"+f"(d[14]),"+f"(d[15]),"+f"(d[16]),"+f"(d[17]),"+f"(d[18]),"+f"(d[19]),"+f"(d[20]),"+f"(d[21]),"+f"(d[22]),"+f"(d[23]),"+f"(d[24]),"+f"(d[25]),"+f"(d[26]),"+f"(d[27]),"+f"(d[28]),"+f"(d[29]),"+f"(d[30]),"+f"(d[31]),"+f"(d[32]),"+f"(d[33]),"+f"(d[34]),"+f"(d[35]),"+f"(d[36]),"+f"(d[37]),"+f"(d[38]),"+f"(d[39]),"+f"(d[40]),"+f"(d[41]),"+f"(d[42]),"+f"(d[43]),"+f"(d[44]),"+f"(d[45]),"+f"(d[46]),"+f"(d[47]),"+f"(d[48]),"+f"(d[49]),"+f"(d[50]),"+f"(d[51]),"+f"(d[52]),"+f"(d[53]),"+f"(d[54]),"+f"(d[55]),"+f"(d[56]),"+f"(d[57]),"+f"(d[58]),"+f"(d[59]),"+f"(d[60]),"+f"(d[61]),"+f"(d[62]),"+f"(d[63]) : "r"(a[0]), "r"(a[1]), "r"(a[2]), "r"(a[3]), "l"(db), "r"(sc));
}
template<> __device__ __forceinline__ void wgmma_rs<96>(float* d, const uint32_t* a, uint64_t db, int sc) {
  asm volatile("{.reg .pred p; setp.ne.b32 p, %53, 0;\n"
   "wgmma.mma_async.sync.aligned.m64n96k16.f32.bf16.bf16 {%0,%1,%2,%3,%4,%5,%6,%7,%8,%9,%10,%11,%12,%13,%14,%15,%16,%17,%18,%19,%20,%21,%22,%23,%24,%25,%26,%27,%28,%29,%30,%31,%32,%33,%34,%35,%36,%37,%38,%39,%40,%41,%42,%43,%44,%45,%46,%47}, {%48,%49,%50,%51}, %52, p, 1, 1, 0;}\n"
   : "+f"(d[0]),"+f"(d[1]),"+f"(d[2]),"+f"(d[3]),"+f"(d[4]),"+f"(d[5]),"+f"(d[6]),"+f"(d[7]),"+f"(d[8]),"+f"(d[9]),"+f"(d[10]),"+f"(d[11]),"+f"(d[12]),"+f"(d[13]),"+f"(d[14]),"+f"(d[15]),"+f"(d[16]),"+f"(d[17]),"+f"(d[18]),"+f"(d[19]),"+f"(d[20]),"+f"(d[21]),"+f"(d[22]),"+f"(d[23]),"+f"(d[24]),"+f"(d[25]),"+f"(d[26]),"+f"(d[27]),"+f"(d[28]),"+f"(d[29]),"+f"(d[30]),"+f"(d[31]),"+f"(d[32]),"+f"(d[33]),"+f"(d[34]),"+f"(d[35]),"+f"(d[36]),"+f"(d[37]),"+f"(d[38]),"+f"(d[39]),"+f"(d[40]),"+f"(d[41]),"+f"(d[42]),"+f"(d[43]),"+f"(d[44]),"+f"(d[45]),"+f"(d[46]),"+f"(d[47]) : "r"(a[0]), "r"(a[1]), "r"(a[2]), "r"(a[3]), "l"(db), "r"(sc));
}
template<> __device__ __forceinline__ void wgmma_rs<64>(float* d, const uint32_t* a, uint64_t db, int sc) {
  asm volatile("{.reg .pred p; setp.ne.b32 p, %37, 0;\n"
   "wgmma.mma_async.sync.aligned.m64n64k16.f32.bf16.bf16 {%0,%1,%2,%3,%4,%5,%6,%7,%8,%9,%10,%11,%12,%13,%14,%15,%16,%17,%18,%19,%20,%21,%22,%23,%24,%25,%26,%27,%28,%29,%30,%31}, {%32,%33,%34,%35}, %36, p, 1, 1, 0;}\n"
   : "+f"(d[0]),"+f"(d[1]),"+f"(d[2]),"+f"(d[3]),"+f"(d[4]),"+f"(d[5]),"+f"(d[6]),"+f"(d[7]),"+f"(d[8]),"+f"(d[9]),"+f"(d[10]),"+f"(d[11]),"+f"(d[12]),"+f"(d[13]),"+f"(d[14]),"+f"(d[15]),"+f"(d[16]),"+f"(d[17]),"+f"(d[18]),"+f"(d[19]),"+f"(d[20]),"+f"(d[21]),"+f"(d[22]),"+f"(d[23]),"+f"(d[24]),"+f"(d[25]),"+f"(d[26]),"+f"(d[27]),"+f"(d[28]),"+f"(d[29]),"+f"(d[30]),"+f"(d[31]) : "r"(a[0]), "r"(a[1]), "r"(a[2]), "r"(a[3]), "l"(db), "r"(sc));
}
template<> __device__ __forceinline__ void wgmma_rs<32>(float* d, const uint32_t* a, uint64_t db, int sc) {
  asm volatile("{.reg .pred p; setp.ne.b32 p, %21, 0;\n"
   "wgmma.mma_async.sync.aligned.m64n32k16.f32.bf16.bf16 {%0,%1,%2,%3,%4,%5,%6,%7,%8,%9,%10,%11,%12,%13,%14,%15}, {%16,%17,%18,%19}, %20, p, 1, 1, 0;}\n"
   : "+f"(d[0]),"+f"(d[1]),"+f"(d[2]),"+f"(d[3]),"+f"(d[4]),"+f"(d[5]),"+f"(d[6]),"+f"(d[7]),"+f"(d[8]),"+f"(d[9]),"+f"(d[10]),"+f"(d[11]),"+f"(d[12]),"+f"(d[13]),"+f"(d[14]),"+f"(d[15]) : "r"(a[0]), "r"(a[1]), "r"(a[2]), "r"(a[3]), "l"(db), "r"(sc));
}

__device__ __forceinline__ void conv_dupA(uint32_t* A, uint32_t zz) {
#pragma unroll
  for (int s = 0; s < 4; s++) {
    asm volatile("xor.b32 %0, %1, %2;" : "=r"(A[4 * s + 3]) : "r"(A[4 * s]), "r"(zz));
    if (s < 3) asm volatile("xor.b32 %0, %1, %2;" : "=r"(A[4 * s + 6]) : "r"(A[4 * s + 1]), "r"(zz));
  }
}
template <int OFF, int DUP = 1> __device__ __forceinline__ void conv_ldA(uint32_t* A, uint32_t ra, uint32_t zz, const uint32_t* Pv = nullptr) {
  if (!SHB || !(OFF & 128)) A[2] = lds32(ra + OFF);
  else if (DUP) asm volatile("xor.b32 %0, %1, %2;" : "=r"(A[2]) : "r"(Pv[13]), "r"(zz));
#pragma unroll
  for (int s = 0; s < 4; s++) { A[4 * s] = lds32(ra + OFF + 32 * s + 16); A[4 * s + 1] = lds32(ra + OFF + 32 * s + 32); }
  if (DUP) conv_dupA(A, zz);
}
template <int N, int H, int ACC = 0> __device__ __forceinline__ void conv_grp(float* T, const uint32_t* A, uint64_t dX) {
  WG_FENCE();
#pragma unroll
  for (int s = 0; s < 4; s++) wgmma_rs<N>(T, A + 4 * s, dX - (4 * H + s), (ACC || H > 0 || s > 0));
  WG_COMMIT();
}
template <int H> __device__ __forceinline__ void conv_grp2(float* T, float* U, const uint32_t* A, uint64_t dX) {
  WG_FENCE();
#pragma unroll
  for (int s = 0; s < 4; s++) {
    wgmma_rs<64>(T, A + 4 * s, dX + 32 - (4 * H + s), (H > 0 || s > 0));
    wgmma_rs<32>(U, A + 4 * s, dX - (4 * H + s), (H > 0 || s > 0));
  }
  WG_COMMIT();
}

__device__ __forceinline__ void red_ld(uint4 (*v)[4], uint32_t pb, int idx) {
#pragma unroll
  for (int n = 0; n < 2; n++)
#pragma unroll
    for (int q = 0; q < 4; q++) { v[n][q] = make_uint4(0, 0, 0, 0); if (n > 0 || idx >= 16 * q) v[n][q] = lds128(pb + idx * 16 + q * 3840 + n * 2048); }
}
__device__ __forceinline__ void red_st(const uint4 (*v)[4], uint32_t zo, int idx) {
#pragma unroll
  for (int m = 0; m < 2; m++)
    sts128(zo + idx * 16 + m * 2048, badd2(badd2(v[m][0].x, v[m][1].x), badd2(v[m][2].x, v[m][3].x)), badd2(badd2(v[m][0].y, v[m][1].y), badd2(v[m][2].y, v[m][3].y)),
           badd2(badd2(v[m][0].z, v[m][1].z), badd2(v[m][2].z, v[m][3].z)), badd2(badd2(v[m][0].w, v[m][1].w), badd2(v[m][2].w, v[m][3].w)));
}
__device__ __forceinline__ void red_fin(uint32_t bar) {
  asm volatile("fence.proxy.async.shared::cta;" ::: "memory");
  mbar_arrive(bar);
}

__global__ void __launch_bounds__(384, 1) fused_kernel(const __grid_constant__ Maps maps, const Ptrs P, const uint32_t zz) {
  extern __shared__ __align__(1024) uint8_t smem[];
  constexpr uint32_t sb = 1024;
  const int tid = threadIdx.x;
  const int b = blockIdx.x;
  const uint32_t bars = sb + SM_BAR;

#define BAR(i) (bars + 8u * (i))
  TR(t63);
  const int rt = (b >> 1) & 15, ct = (b & 1) | ((b >> 5) << 1);
  const int rb = b >> 2, cb = b & 3;
  const int b2 = cb * 32 + rb;
  const int ch0 = cb * 160 + rb;

  if ((tid >> 5) == 8) {
    if (elect_one()) {
      mbar_init(BAR(B_FX), 1); mbar_init(BAR(B_FW), 1); mbar_init(BAR(B_FW + 1), 1);
      asm volatile("fence.proxy.async.shared::cta;" ::: "memory");
      mbar_expect_tx(BAR(B_FX), 16384); tma2d(sb + SM_X, &maps.x, BAR(B_FX), 0, rt * 128);
#pragma unroll
      for (int n = 0; n < NPRE; n++) {
        mbar_expect_tx(BAR(B_FW + n), 24576);
        tma3d(sb + SM_W + n * 24576, &maps.wg, BAR(B_FW + n), 0, n * 32, ct * 3); tma3d(sb + SM_W + n * 24576 + 12288, &maps.wu, BAR(B_FW + n), 0, n * 32, ct * 3);
      }
      mbar_init(BAR(B_FX + 1), 1); mbar_init(BAR(B_FX + 2), 1); mbar_init(BAR(B_FW + 2), 1);
      asm volatile("fence.proxy.async.shared::cta;" ::: "memory");
    }
  }
  const int wg = __shfl_sync(0xffffffffu, tid >> 7, 0);

  if (wg == 2) {
    asm volatile("setmaxnreg.dec.sync.aligned.u32 40;");
    bar_sync(0, 384);
    const int warp = __shfl_sync(0xffffffffu, tid >> 5, 0) - 8, lane = tid & 31;
    if (warp == 0) {
      if (elect_one()) {

#pragma unroll
        for (int n = NPRE; n < 20; n++) {
          const int k = n < 14 ? (n >> 1) : n < 17 ? n - 7 : n - 10;
          const bool up = n < 14 ? (n & 1) : (n >= 17);
          if (n == PF_N) { tma3d_prefetch(&maps.wu, 0, 576, ct * 3); tma3d_prefetch(&maps.wu, 0, 608, ct * 3); }
          if (n == PF8) { tma3d_prefetch(&maps.wu, 0, 512, ct * 3); tma3d_prefetch(&maps.wu, 0, 544, ct * 3); }
          if (!up && n != 16) {
            const int xs = k % 3;
            if (k >= 3) mbar_wait(BAR(B_EX + xs), ((k / 3) - 1) & 1);
            mbar_expect_tx(BAR(B_FX + xs), 16384);
            tma2d(sb + SM_X + xs * 16384, &maps.x, BAR(B_FX + xs), k * 64, rt * 128);
          }
          const int s = n % 5;
          if (n >= 5) mbar_wait(BAR(B_EW + s), ((n / 5) - 1) & 1);
          mbar_expect_tx(BAR(B_FW + s), 24576);
          tma3d(sb + SM_W + s * 24576, n >= 17 ? &maps.wu : &maps.wg, BAR(B_FW + s), 0, n < 14 ? n * 32 : k * 64, ct * 3);
          tma3d(sb + SM_W + s * 24576 + 12288, n < 14 || n >= 17 ? &maps.wu : &maps.wg, BAR(B_FW + s), 0, n < 14 ? n * 32 : k * 64 + 32, ct * 3);
          if (n == X9_N) {
            mbar_expect_tx(BAR(B_F9), 16384);
            tma2d(sb + SM_GAP, &maps.x, BAR(B_F9), 576, rt * 128);
          }
          if (n == KV0 || n == KV1 || n == KV2 || n == KV3 || n == KV4) {
            const int r = n == KV0 ? 0 : n == KV1 ? 1 : n == KV2 ? 2 : n == KV3 ? 3 : 4;
            mbar_expect_tx(BAR(B_KV + r), 8576);
            tma3d(sb + SM_D + r * 8576, &maps.k, BAR(B_KV + r), 0, (b >> 1) * 32 - 3, (b & 1) * 10 + 2 * r);
            tma3d(sb + SM_D + r * 8576 + 4480, &maps.v, BAR(B_KV + r), 0, (b >> 1) * 32, (b & 1) * 10 + 2 * r);
          }
          if (n >= SK_N && n < SK_N + 5) l2_prefetch(P.ssm_k + (size_t)(ch0 + 32 * (n - SK_N)) * 2048, 4096);
          if (n == WD_N && b < 120) tma3d_prefetch(&maps.wd, 0, (b / 5) * 64, (b % 5) * 4);
          if (n == WL_N) {
            mbar_wait(BAR(B_EX), 0);
            mbar_expect_tx(BAR(B_WD), b < 120 ? 16384 : 0);
            if (b < 120) tma3d(sb + SM_X, &maps.wd, BAR(B_WD), 0, (b / 5) * 64, (b % 5) * 4);
          }
        }
        TS1(32);
        mbar_wait(BAR(B_PRE), 0);
        const uint32_t target = lds32v(sb + SM_BAR + 576);
        mbar_wait(BAR(B_EW + 0), 1);
        flag_wait(&g_cnt[0], target);
        mbar_expect_tx(BAR(B_XI), 5 * XCH);
        tma3d(sb + SM_W, &maps.xl, BAR(B_XI), 0, -2, b2 * 10);
        TS1(1);
        const uint8_t* wsrc = g_wd + cb * 20480;
        flag_wait(&g_cnt[45 * 32], target);
        TS1(33);
        mbar_wait(BAR(B_G1), 0);
        for (int s = 0; s < 4; s++) {
          mbar_expect_tx(BAR(B_F2 + s), 28672);
          bulk_g2s(sb + SM_R2 + s * 28672 + 8192, wsrc + s * 81920, 20480, BAR(B_F2 + s));
        }
        TS1(2);
        flag_wait(&g_cnt[(1 + rb) * 32], target);
        TS1(3);
        const uint8_t* hsrc = g_h + (size_t)rb * 24 * 8192;
        for (int s = 0; s < 4; s++) {
          if (!(s & 1)) mbar_wait(BAR(B_KV + (s >> 1)), 1);
          bulk_g2s(sb + SM_R2 + s * 28672, hsrc + s * 8192, 8192, BAR(B_F2 + s));
        }
        mbar_expect_tx(BAR(B_Q), 256);
        bulk_g2s(sb + SM_GT, g_gate + rb * 64, 256, BAR(B_Q));
        tmap_prefetch(&maps.z);
        {
          uint32_t tick = 0;
          int cc = 4;
#pragma unroll
          for (int c = 4; c < 24; c++) {
            const int s = g2s(c);
            const uint8_t* pa = hsrc + cc * 8192;
            const uint8_t* pw = wsrc + cc * 81920;
            if (c > RS) { for (int it = 0; (int)(clk() - tick) < 0 && it < 200; it++) {} tick += PER; }
            if (c == 4) { mbar_wait(BAR(B_HF + 1), 0); mbar_wait(BAR(B_ZR + 2), 0); }
            else if (c == XS) mbar_wait(BAR(B_KV + 3), 1);
            else if (SPN & 1) mbar_spin(BAR(B_E2 + s), (g2u(c) - 1) & 1);
            else mbar_wait(BAR(B_E2 + s), (g2u(c) - 1) & 1);
            if (c == RS) {
              const uint32_t q = (clk() + TDEL) / PER + TICK;
              tick = q * PER; cc = RS + q % (24 - RS);
              pa = hsrc + cc * 8192; pw = wsrc + cc * 81920;
              for (int it = 0; (int)(clk() - tick) < 0 && it < 200; it++) {}
              tick += PER;
            }
            bulk_g2s(sb + g2b(s), pw, 20480 - FAKE, BAR(B_F2 + s));
            bulk_g2s(sb + g2a(s), pa, 8192, BAR(B_F2 + s));
            mbar_expect_tx(BAR(B_F2 + s), 28672 - FAKE);
            if (++cc == 24) cc = RS;
          }
        }
        TS1(4);
      }
    } else {
      const int hw = warp - 1;
      if (hw == 2) {
        if (smem_u32(smem) != sb) asm volatile("trap;");
        const int c8 = lane & 7, r4 = lane >> 3;
        float acc[4] = {0.f, 0.f, 0.f, 0.f};
        uint4 gw = __ldg((const uint4*)(P.gate_w + c8 * 8));
        gw.x |= __ldg((const uint32_t*)(P.gate_w + 128 + lane * 16)) & zz;
        uint32_t xs = 0, xph = 0;
        const __nv_bfloat16* pw = (lane & 1 ? P.wu : P.wg) + (rt * 4 + (lane >> 3)) * 1536 + ct * 192 + ((lane >> 1) & 3) * 64;
        const __nv_bfloat16* px = P.x + (rt * 128 + ct * 16 + (lane & 15)) * 640;
        const bool pfw = (lane & 6) != 6;
#define PFK(kk) { if (pfw) asm volatile("prefetch.global.L2 [%0];" ::"l"(pw + (kk) * 98304)); if (lane < 16) asm volatile("prefetch.global.L2 [%0];" ::"l"(px + (kk) * 64)); }
        for (int k = PF0; k < PD; k++) PFK(k)
#pragma unroll 1
        for (int k = 0; k < 10; k++) {
          const uint4 gn = __ldg((const uint4*)(P.gate_w + (k < 9 ? k + 1 : 0) * 64 + c8 * 8));
          if (k == 9) { xs = 3; mbar_wait(BAR(B_F9), 0); } else mbar_wait(BAR(B_FX + xs), xph);
          if (k + PD < 10) PFK(k + PD)
#pragma unroll
          for (int i = 0; i < 4; i++) {
            const int row = (i >> 1) * 64 + ct * 8 + (i & 1) * 4 + r4;
            const uint4 v = lds128(sb + SM_X + xs * 16384 + row * 128 + ((c8 ^ (row & 7)) << 4));
            const uint32_t p[4] = {bmul2(v.x, gw.x), bmul2(v.y, gw.y), bmul2(v.z, gw.z), bmul2(v.w, gw.w)};
#pragma unroll
            for (int e = 0; e < 4; e++) acc[i] += __uint_as_float(p[e] << 16) + __uint_as_float(p[e] & 0xffff0000u);
          }
          __syncwarp();
          if (lane == 0 && k < 7) mbar_arrive(BAR(B_EX + xs));
          __syncwarp();
          if (++xs == 3) { xs = 0; xph ^= 1; }
          gw = gn;
        }
#pragma unroll
        for (int i = 0; i < 4; i++)
#pragma unroll
          for (int o = 1; o < 8; o <<= 1) acc[i] += __shfl_xor_sync(0xffffffffu, acc[i], o);
        if (c8 < 4) {
          const float sv = c8 == 0 ? acc[0] : c8 == 1 ? acc[1] : c8 == 2 ? acc[2] : acc[3];
          const float l = __bfloat162float(__float2bfloat16_rn(sv));
          const float gv = __bfloat162float(__float2bfloat16_rn(1.0f / (1.0f + __expf(-l))));
          asm volatile("st.shared.f32 [%0], %1;" ::"r"(sb + SM_GO + c8 * 16 + r4 * 4), "f"(gv) : "memory");
          asm volatile("fence.proxy.async.shared::cta;" ::: "memory");
        }
        __syncwarp();
        if (lane == 0) { mbar_arrive(BAR(B_G1)); mbar_arrive(BAR(B_HS + 0)); mbar_arrive(BAR(B_HS + 1)); TS1(7); }
      } else {
        const int ht = tid - 288;
        const int rc = b >> 1, chb = (b & 1) * 320;
        const int cl = hw * 32 + (lane >> 1) * 2;
        const __nv_bfloat16* skp = P.shift_k + (chb + cl) * 4;
        uint4 sk = __ldg((const uint4*)skp);
        if (ht < 20) asm volatile("prefetch.global.L2 [%0];" ::"l"(P.shift_k + chb * 4 + ht * 64));
        uint32_t ka = sb + SM_D + hw * 2240 + (lane >> 1) * 4 + (lane & 1) * 1024;
        const uint32_t vo = 4480 - hw * 192, so = 4480 - hw * 192 + (lane >> 1) * 28 - (lane & 1) * 1008;
#pragma unroll 1
        for (int pg = 0; pg < 5; pg++) {
          const uint32_t w0 = __byte_perm(sk.x, sk.z, 0x5410), w1 = __byte_perm(sk.x, sk.z, 0x7632);
          const uint32_t w2 = __byte_perm(sk.y, sk.w, 0x5410), w3 = __byte_perm(sk.y, sk.w, 0x7632);
          sk = __ldg((const uint4*)(skp + (pg < 4 ? pg + 1 : 0) * 256));
          mbar_wait(BAR(B_KV + pg), 0);
          if (ht == 0) TS1(21 + pg);
          uint32_t kk[19], o[8];
#pragma unroll
          for (int i = 0; i < 11; i++) kk[i] = lds32(ka + i * 64);
#pragma unroll
          for (int h = 0; h < 2; h++) {
#pragma unroll
            for (int i = 0; i < 8; i++) o[i] = lds32(ka + vo + (8 * h + i) * 64);
#pragma unroll
            for (int i = 0; i < 8; i++) o[i] = bmul2(bfma2(kk[8 * h + i + 3], w0, bfma2(kk[8 * h + i + 2], w1, bfma2(kk[8 * h + i + 1], w2, bmul2(kk[8 * h + i], w3)))), o[i]);
            if (h == 0) {
#pragma unroll
              for (int i = 11; i < 19; i++) kk[i] = lds32(ka + i * 64);
            }
            __syncwarp();
            sts128(ka + so + h * 512, __byte_perm(o[1], o[0], 0x5410), __byte_perm(o[3], o[2], 0x5410), __byte_perm(o[5], o[4], 0x5410), __byte_perm(o[7], o[6], 0x5410));
            sts128(ka + so + h * 512 + 1024, __byte_perm(o[1], o[0], 0x7632), __byte_perm(o[3], o[2], 0x7632), __byte_perm(o[5], o[4], 0x7632), __byte_perm(o[7], o[6], 0x7632));
          }
          asm volatile("fence.proxy.async.shared::cta;" ::: "memory");
          __syncwarp();
          if (lane == 0) {
            const int blk = (b & 1) * 10 + 2 * pg + hw;
            asm volatile("cp.async.bulk.tensor.5d.global.shared::cta.bulk_group [%0, {%2,%3,%3,%3,%4}], [%1];" ::"l"(&maps.xs), "r"(ka + vo), "r"(rc * 16), "r"(0), "r"((blk / 5) * 160 + blk % 5) : "memory");
          }
          ka += 8576;
        }
        if (lane == 0) {
          asm volatile("cp.async.bulk.commit_group;" ::: "memory");
          asm volatile("cp.async.bulk.wait_group.read 0;" ::: "memory");
        }
        bar_sync(3, 64);
        if (ht == 0) {
          TS1(12);
          mbar_expect_tx(BAR(B_HR), 20480);
          for (int c = 0; c < 5; c++) bulk_g2s(sb + SM_D + 128 + c * TP + 4128, P.ssm_k + (size_t)(ch0 + 32 * c) * 2048, 4096, BAR(B_HR));
        }
        uint32_t old = 0;
        if (lane == 0) {
          asm volatile("cp.async.bulk.wait_group 0;" ::: "memory");
          mbar_arrive(BAR(B_KD));
          if (hw) {
            TS1(6);
            mbar_wait(BAR(B_KD), 0);
            TS1(20);
            asm volatile("atom.relaxed.gpu.global.add.u32 %0, [%1], 1;" : "=r"(old) : "l"(&g_cnt[0]) : "memory");
          }
        }
        __syncwarp();
        if (lane < 20) sts128(sb + SM_D + 96 + (lane >> 2) * TP + ((lane >> 1) & 1) * 4128 + (lane & 1) * 16, 0, 0, 0, 0);
        uint32_t dv = 0;
        if (ht < 5) dv = __ldg((const unsigned short*)(P.ssm_D + ch0 + 32 * ht));
        if (lane == 0) TS1(hw ? 9 : 10);
        mbar_wait(BAR(B_HR), 0);
        if (ht == 0) TS1(11);
        if (ht < 5) {
          const uint32_t a0 = sb + SM_D + 128 + 4128 + ht * TP;
          asm volatile("st.shared.u32 [%0], %1;" ::"r"(a0), "r"(badd2(lds32(a0), dv)) : "memory");
        }
        __syncwarp();
        if (ht == 32) TS1(13);
#pragma unroll 1
        for (int c = 0; c < 5; c++) {
          const uint32_t d = sb + SM_D + 128 + c * TP + hw * 2048 + lane * 16;
          uint4 v[4]; uint32_t pv[4];
#pragma unroll
          for (int i = 0; i < 4; i++) { v[i] = lds128(d + 4128 + i * 512); pv[i] = lds32(d + 4124 + i * 512); }
#pragma unroll
          for (int i = 0; i < 4; i++)
            sts128(d + i * 512, __byte_perm(pv[i], v[i].x, 0x5432), __byte_perm(v[i].x, v[i].y, 0x5432), __byte_perm(v[i].y, v[i].z, 0x5432), __byte_perm(v[i].z, v[i].w, 0x5432));
          if (c == 1 && ht == 32) { asm volatile("st.shared.u32 [%0], %1;" ::"r"(sb + SM_BAR + 576), "r"((old & ~127u) + 128u) : "memory"); mbar_arrive(BAR(B_PRE)); TS1(8); }
        }
        __syncwarp();
        if (lane == 0) { mbar_arrive(BAR(B_HC)); if (hw) TS1(14); }
        __syncwarp();
        mbar_wait(BAR(B_WD), 0);
        if (ht == 32) TS1(34);
        {
          const uint32_t wl = (lane & 7) * 64 + (((lane >> 3) ^ ((lane & 7) >> 1)) << 4);
          const uint32_t wd = (lane >> 2) * 64 + (((lane ^ (lane >> 3)) & 3) << 4) - wl;
          uint32_t wa = sb + SM_X + hw * 8192 + wl;
#pragma unroll 1
          for (int i = 0; i < 16 / WU; i++, wa += WU * 512) {
            uint4 v[WU];
#pragma unroll
            for (int e = 0; e < WU; e++) v[e] = ldsm4(wa + e * 512);
#pragma unroll
            for (int e = 0; e < WU; e++) sts128(wa + wd + e * 512, v[e].x, v[e].y, v[e].z, v[e].w);
          }
        }
        asm volatile("fence.proxy.async.shared::cta;" ::: "memory");
        bar_sync(3, 64);
        if (ht == 32) {
          TS1(35);
          if (b < 120) bulk_s2g(g_wd + (size_t)b * 16384, sb + SM_X, 16384);
          asm volatile("cp.async.bulk.commit_group;" ::: "memory");
          asm volatile("cp.async.bulk.wait_group 0;" ::: "memory");
          mbar_arrive(BAR(B_WP));
          flag_add_relaxed(&g_cnt[45 * 32], 1);
          TS1(29);
        }
        if (lane == 0) {
          mbar_wait(BAR(B_HS + hw), 0);
          TS1(5 + hw * 10);
          bulk_s2g(g_h + ((size_t)(rt * 2 + hw) * 24 + ct * 3) * 8192, sb + SM_W + (1 + hw) * 24576, 24576);
          bulk_s2g(g_gate + rt * 128 + hw * 64 + ct * 8, sb + SM_GO + hw * 32, 32);
          asm volatile("cp.async.bulk.commit_group;" ::: "memory");
          asm volatile("cp.async.bulk.wait_group.read 0;" ::: "memory");
          mbar_arrive(BAR(B_HF + hw));
          asm volatile("cp.async.bulk.wait_group 0;" ::: "memory");
          flag_add_relaxed(&g_cnt[(1 + rt * 2 + hw) * 32], 16);
          TS1(26 + hw);
        }
        __syncwarp();
      }
      if (tid == 320) {
#pragma unroll 1
        for (int c = 0; c < 5; c++) {
          mbar_wait(BAR(B_ZR + c), 0);
          TS1(c < 4 ? 16 + c : 28);
          const uint32_t ps = sb + (c >= RM ? SM_D + 128 + c * TP : c < 2 ? SM_R2 + c * 57344 : SM_W + 24576), pp = c < 2 ? 28672 : 8192;
          uint8_t* zd = g_z + (size_t)(ch0 + 32 * c) * 4096;
          bulk_s2g(zd, ps, 4096);
          asm volatile("cp.async.bulk.commit_group;" ::: "memory");
          if (c == 1) {
            mbar_expect_tx(BAR(B_Q), 16384);
            for (int i = 0; i < 4; i++) tma3d(sb + SM_D + i * 4096, &maps.q, BAR(B_Q), 0, rb * 64, cb * 5 + i);
          }
          if (c < RM) {
            asm volatile("cp.async.bulk.wait_group 0;" ::: "memory");
#pragma unroll
            for (int i = 1; i < 4; i++)
              asm volatile("cp.reduce.async.bulk.global.shared::cta.bulk_group.add.noftz.bf16 [%0], [%1], %2;" ::"l"(zd + i * 256), "r"(ps + (i >> 1) * pp + (i & 1) * 4096), "r"(4096 - i * 256) : "memory");
            asm volatile("cp.async.bulk.commit_group;" ::: "memory");
          }
          asm volatile("cp.async.bulk.wait_group.read 0;" ::: "memory");
          mbar_arrive(BAR(B_KV + c));
          if (c == 1) TS1(23);
          asm volatile("cp.async.bulk.wait_group 0;" ::: "memory");
          if (c == 0 || c >= 3) flag_add_relaxed(&g_cnt[(c ? 25 + c * 4 + cb : 33 + cb) * 32], 4);
        }
        TS1(30);
      }
      if (tid == 288) {
        mbar_wait(BAR(B_PRE), 0);
        const uint32_t target = lds32v(sb + SM_BAR + 576);
        mbar_wait(BAR(B_KV + 2), 1);
        mbar_expect_tx(BAR(B_Z), 20480);
        mbar_expect_tx(BAR(B_Z + 1), 4096);
        tma3d(sb + SM_D + 16384, &maps.q, BAR(B_Z), 0, rb * 64, cb * 5 + 4);
        flag_wait(&g_cnt[(33 + cb) * 32], target);
        TS1(21);
        tma2d(sb + SM_D + 20480, &maps.z, BAR(B_Z), rb * 64, cb * 160);
        flag_wait(&g_cnt[(37 + cb) * 32], target);
        TS1(22);
        mbar_wait(BAR(B_ZR + 4), 0);
        uint32_t t0 = clk();
#pragma unroll 1
        for (int c = 1; c < 4; c++) {
          if (ZP && c > 1) { t0 += ZP; for (int it = 0; (int)(clk() - t0) < 0 && it < 200; it++) __nanosleep(20); }
          tma2d(sb + SM_W + (c - 1) * 4096, &maps.z, BAR(B_Z), rb * 64, cb * 160 + 32 * c);
        }
        TS1(24);
        flag_wait(&g_cnt[(41 + cb) * 32], target);
        TS1(31);
        tma2d(sb + SM_W + 12288, &maps.z, BAR(B_Z + 1), rb * 64, cb * 160 + 128);
      }
    }
  } else {
    {
      uint32_t tq;
      asm volatile("mov.u32 %0, %%tid.x;" : "=r"(tq));
      const int wi = __shfl_sync(0xffffffffu, tq >> 5, 0);
      if (elect_one()) {
#pragma unroll 1
        for (int gi = wi + 1; gi < 12; gi += 8) {
          const uint32_t cnt = gi < 5 ? 1 : (uint32_t)(0x80808102040908ull >> (8 * (gi - 5))) & 0xff;
#pragma unroll
          for (int j = 0; j < 6; j++) mbar_init(BAR(gi * 6 + j), cnt);
        }
        asm volatile("fence.proxy.async.shared::cta;" ::: "memory");
      }
      __syncwarp();
    }
    bar_sync(0, 384);
    asm volatile("setmaxnreg.inc.sync.aligned.u32 232;");
    const int t128 = tid & 127, w = __shfl_sync(0xffffffffu, t128 >> 5, 0), lane = tid & 31;
    const uint32_t ra0 = sb + SM_D + 128 + (((lane >> 2) & 1) ? 4128 + 2 * (128 * w + (lane >> 2) - 2 * (lane & 3) - 9) : 2 * (128 * w + (lane >> 2) - 2 * (lane & 3) - 8));
    uint32_t A0[16], A1[16], A2[16];
    {
      float ag[96], au[96];
      const uint64_t dA0 = mkdesc(sb + SM_X + wg * 8192, 16, 1024, 1);
      const uint64_t dB0 = mkdesc(sb + SM_W, 4096, 1024, 1);
      const uint32_t xa = sb + SM_X + wg * 8192 + (16 * w + (lane & 15)) * 128 + (((lane >> 4) ^ (lane & 7)) << 4);
      uint4 A[2];
      TS(18);
      mbar_wait(BAR(B_FX + 0), 0);
      TS(19);
      A[0] = ldsm4(xa);
#pragma unroll
      for (int st = 0; st < 28; st++) {
        const int k = st >> 2, kk = st & 3, n = st >> 1, xs = k % 3;
        if (!(st & 1)) mbar_wait(BAR(B_FW + n % 5), (n / 5) & 1);
        if (LSTEP && st > 0 && st % (LSTEP + !LSTEP) == 0) bar_sync(7, 256);
        if (kk == 0) TS(20 + k);
        if (st == SW && wg) {
          if (st == 26) {
            WG_WAIT(0);
            A[1] = ldsm4((xa ^ (3 << 5)) + xs * 16384);
            if (lane == 0) mbar_arrive(BAR(B_EW + (n - 1) % 5));
          }
          if (lane == 0) mbar_arrive(BAR(B_EX + xs) + ((A[0].x | A[1].x) & zz));
          bar_sync(4, 256);
        }
        WG_FENCE();
        wgmma_rs_tb_n192(ag, A[st & 1], dB0 + (n % 5) * 1536 + (st & 1) * 128, st > 0);
        wgmma_rs_tb_n192(au, A[st & 1], dB0 + (n % 5) * 1536 + 768 + (st & 1) * 128, st > 0);
        WG_COMMIT();
        if (kk == 3 && lane == 0 && !(k == 6 && SW < 28 && wg)) mbar_arrive(BAR(B_EX + xs));
        WG_WAIT(1);
        if (!(st & 1) && st > 0 && lane == 0 && !(st == SW && wg)) mbar_arrive(BAR(B_EW + (n - 1) % 5));
        if (kk < 3) { if (!(st == 26 && SW == 26 && wg)) A[(kk + 1) & 1] = ldsm4((xa ^ ((kk + 1) << 5)) + xs * 16384); }
        else if (k < 6) { mbar_wait(BAR(B_FX + (k + 1) % 3), ((k + 1) / 3) & 1); A[0] = ldsm4(xa + ((k + 1) % 3) * 16384); }
      }
      TS(1);
#define G1_UNITS(acc, xsl, wsl) { WG_FENCE(); _Pragma("unroll") for (int kk = 0; kk < 4; kk++) { wgmma_ss_tb_n192(acc, dA0 + (xsl) * 1024 + kk * 2, dB0 + (wsl) * 1536 + (kk >> 1) * 768 + (kk & 1) * 128, 1); if (kk == 3 - HOFF) WG_COMMIT(); } WG_COMMIT(); }
#define G1_UNIT(acc, xsl, wsl) { WG_FENCE(); _Pragma("unroll") for (int kk = 0; kk < 4; kk++) wgmma_ss_tb_n192(acc, dA0 + (xsl) * 1024 + kk * 2, dB0 + (wsl) * 1536 + (kk >> 1) * 768 + (kk & 1) * 128, 1); WG_COMMIT(); }
      mbar_wait(BAR(B_FX + 1), 0);
      mbar_wait(BAR(B_FW + 4), 0);
      if (SW == 28 && wg) {
        WG_WAIT(0);
        if (lane == 0) mbar_arrive(BAR(B_EW + 3));
        bar_sync(4, 256);
      }
      TS(8);
      G1_UNIT(ag, 1, 4);
      WG_WAIT(1);
      if (lane == 0 && (SW < 28 || !wg)) mbar_arrive(BAR(B_EW + 3));
      mbar_wait(BAR(B_FX + 2), 0);
      mbar_wait(BAR(B_FW + 0), 1);
      TS(6);
      G1_UNIT(ag, 2, 0);
      WG_WAIT(1);
      if (lane == 0) mbar_arrive(BAR(B_EW + 4));
      TS(9);
      mbar_wait(BAR(B_F9), 0);
      mbar_wait(BAR(B_FW + 1), 1);
      TS(16);
      G1_UNITS(ag, 3, 1);
      WG_WAIT(1);
      bar_arrive(4 + wg, 256);
      TS(14);
      if (lane == 0) mbar_arrive(BAR(B_EW + 0));
      WG_WAIT(0);
      if (lane == 0) mbar_arrive(BAR(B_EW + 1));
      TS(2);
      uint32_t sg[48], dep;
#define SIG(lo, hi) dep = sig_range<lo, hi>(ag, sg, zz);
      SIG(0, SG0)
      TS(15);
      mbar_wait(BAR(B_FW + 2) + dep, 1);
      mbar_wait(BAR(B_FW + 3), 1);
      bar_sync(5 + wg, 256);
      TS(17);
      WG_FENCE();
#define U1(xsl, wsl, kk) wgmma_ss_tb_n192(au, dA0 + (xsl) * 1024 + kk * 2, dB0 + ((wsl) * 1536 + (kk >> 1) * 768 + (kk & 1) * 128 + dep), 1);
#define SGC(n) ((SG0 + (n) * SG1) < 48 ? (SG0 + (n) * SG1) : 48)
      U1(1, 2, 0) U1(1, 2, 1) U1(1, 2, 2) SIG(SGC(0), SGC(1))
      U1(1, 2, 3) WG_COMMIT(); SIG(SGC(1), SGC(2))
      U1(2, 3, 0) SIG(SGC(2), SGC(3))
      U1(2, 3, 1) SIG(SGC(3), SGC(4))
      U1(2, 3, 2) SIG(SGC(4), SGC(5))
      U1(2, 3, 3) WG_COMMIT(); SIG(SGC(5), 48)
      WG_WAIT(1);
      if (lane == 0) mbar_arrive(BAR(B_EW + 2));
      TS(10);
      mbar_wait(BAR(B_FW + 4) + dep, 1);
      TS(12);
      G1_UNITS(au, 3, 4);
      mbar_wait(BAR(B_HC), 0);
      conv_ldA<0, 0>(A0, ra0 + wg * TP, zz); conv_ldA<128, 0>(A1, ra0 + wg * TP, zz);
      WG_WAIT(1);
      if (!wg) bar_arrive(6, 256);
      TS(3);
      mbar_wait(BAR(B_EW + 1 + wg), 1);
      WG_WAIT(0);
      if (lane == 0) mbar_arrive(BAR(B_G1));
      TS(4);
      const uint32_t hb = sb + SM_W + (1 + wg) * 24576 + (16 * w + (lane & 15)) * 128;
#pragma unroll
      for (int j = 0; j < 24; j += 2) {
        uint32_t p[4];
#pragma unroll
        for (int e = 0; e < 4; e++) p[e] = bmul2(sg[2 * j + e], pack_bf16(au[4 * j + 2 * e], au[4 * j + 2 * e + 1]));
        const int cc = (j & 7) + (lane >> 4);
        stsm4(hb + (j >> 3) * 8192 + ((cc ^ (lane & 7)) << 4), p[0], p[1], p[2], p[3]);
      }
      asm volatile("fence.proxy.async.shared::cta;" ::: "memory");
      mbar_arrive(BAR(B_HS + wg));
      TS(5);
    }
      uint32_t pb = sb + SM_R2 + wg * 57344, pitch = 28672;
      const uint32_t po = (w & 1) * 4096 + (lane >> 4) * 256 + (lane & 4) * 32 + (((lane >> 1) ^ lane) & 4) * 16 + (lane & 3) * 16;
      mbar_wait(BAR(B_XI), 0);
      conv_dupA(A0, zz); conv_dupA(A1, zz);
      if (SHB) asm volatile("xor.b32 %0, %1, %2;" : "=r"(A1[2]) : "r"(A0[13]), "r"(zz));
#pragma unroll 1
      for (int c = wg; c < 4; c += 2) {
        const uint32_t ra = ra0 + c * TP;
        const uint64_t dX = mkdesc(sb + SM_W + c * XCH + 256, XP, 128, 0);
        float T0[64], T1[16], T2[32], T3[16];
        TS(27 + (c >> 1));
        WG_FENCE();
#pragma unroll
        for (int s = 0; s < 8; s++) {
          wgmma_rs<128>(T0, (s < 4 ? A0 : A1 - 16) + 4 * s, dX - s, s > 0);
          if (s == 3 || s == 7) WG_COMMIT();
        }
        if (c >= 2) { pb = sb + SM_W + (1 + wg) * 24576; pitch = 8192; }
        conv_ldA<3072>(A2, ra, zz);
        conv_grp<32, 0>(T3, A2, dX);
        WG_WAIT(2); conv_ldA<3072 + 128>(A0, ra, zz, A2);
        conv_grp<32, 1>(T3, A0, dX);
        WG_WAIT(2); conv_ldA<1024>(A1, ra, zz);
        conv_grp2<0>(T2, T1, A1, dX);
        WG_WAIT(2); conv_ldA<1024 + 128>(A2, ra, zz, A1);
        conv_grp2<1>(T2, T1, A2, dX);
        WG_WAIT(2); conv_ldA<2048>(A0, ra, zz);
        conv_grp<64, 0, 1>(T2, A0, dX);
#pragma unroll
        for (int i = 0; i < 16; i++) fadd_v(T0[48 + i], T3[i]);
        WG_WAIT(2); conv_ldA<2048 + 128>(A1, ra, zz, A0);
        conv_grp<64, 1>(T2, A1, dX);
        WG_WAIT(2);
#pragma unroll
        for (int i = 0; i < 16; i++) fadd_v(T0[16 + i], T1[i]);
        const uint32_t rn = c < 2 ? ra + 2 * TP : ra0 + 4 * TP + (wg ? 0 : 1024);
        WG_WAIT(1); conv_ldA<0>(A0, rn, zz);
        mbar_wait(BAR(c < 2 ? B_G1 : B_HF + wg), 0);
        if (c == 1) mbar_wait(BAR(B_WP), 0);
        const uint32_t pa = pb + po + (w >> 1) * pitch;
#pragma unroll
        for (int j = 0; j < 8; j += 2)
          stsm4t(pa + j * 256, pack_bf16(T0[4 * j], T0[4 * j + 1]), pack_bf16(T0[4 * j + 2], T0[4 * j + 3]), pack_bf16(T0[4 * j + 4], T0[4 * j + 5]), pack_bf16(T0[4 * j + 6], T0[4 * j + 7]));
        WG_WAIT(0); conv_ldA<128>(A1, rn, zz, A0);
        TS(30 + (c >> 1));
#pragma unroll
        for (int i = 0; i < 32; i++) T0[32 + i] += T2[i];
#pragma unroll
        for (int j = 8; j < 16; j += 2)
          stsm4t(pa + j * 256, pack_bf16(T0[4 * j], T0[4 * j + 1]), pack_bf16(T0[4 * j + 2], T0[4 * j + 3]), pack_bf16(T0[4 * j + 4], T0[4 * j + 5]), pack_bf16(T0[4 * j + 6], T0[4 * j + 7]));
        if (c < RM) red_fin(BAR(B_ZR + c));
      }
      const uint32_t ra = ra0 + 4 * TP;
      const uint64_t dX = mkdesc(sb + SM_W + 4 * XCH + 256, XP, 128, 0);
      uint4 v[2][4];
      TS(29);
#define PST(pa, T, j) stsm4t(pa, pack_bf16(T[4 * (j)], T[4 * (j) + 1]), pack_bf16(T[4 * (j) + 2], T[4 * (j) + 3]), pack_bf16(T[4 * (j) + 4], T[4 * (j) + 5]), pack_bf16(T[4 * (j) + 6], T[4 * (j) + 7]))
    const int g = lane >> 2;
    const int frow = 16 * w + (lane & 7) + 8 * ((lane >> 3) & 1);
    const uint32_t fo = frow * 64 + (((lane >> 4) ^ ((frow >> 1) & 3)) << 4);

    if (wg == 0) {
      float acc[80];
      const uint64_t dA0 = mkdesc(sb, 16, 1024, 1), dB0 = mkdesc(sb, 4096, 512, 2);
      {
        float T1[16], T2[32];
        WG_FENCE();
#pragma unroll
        for (int s = 0; s < 8; s++) {
          wgmma_rs<64>(T2, (s < 4 ? A0 : A1 - 16) + 4 * s, dX + 32 - s, s > 0);
          wgmma_rs<32>(T1, (s < 4 ? A0 : A1 - 16) + 4 * s, dX - s, s > 0);
          if (s == 3 || s == 7) WG_COMMIT();
          if (RM <= 2) {
            if (s == RQ0) { bar_sync(1, 128); red_ld(v, sb + SM_W + 24576, t128); }
            if (s == RQ1) red_st(v, sb + SM_D + 128 + 2 * TP, t128);
            if (s == RQ2) { red_fin(BAR(B_ZR + 2)); TS(34); }
          }
        }
        conv_ldA<2048>(A2, ra, zz);
        conv_grp<64, 0, 1>(T2, A2, dX);
        WG_WAIT(2); conv_ldA<2048 + 128>(A0, ra, zz, A2);
        conv_grp<64, 1>(T2, A0, dX);
        bar_sync(8, 256);
        const uint32_t pa = sb + SM_W + po + (w >> 1) * 8192 + 1024;
        WG_WAIT(2);
        PST(pa, T1, 0); PST(pa + 512, T1, 2);
        mbar_wait(BAR(B_F2), 0);
        WG_FENCE();
#pragma unroll
        for (int kk = 0; kk < 4; kk++) wgmma_ss_tb_n160(acc, dA0 + (g2a(0) / 16 + kk * 2), dB0 + (g2b(0) / 16 + kk * 64), kk > 0);
        WG_COMMIT();
        WG_WAIT(1);
        TS(32);
#pragma unroll
        for (int j = 0; j < 8; j += 2) PST(pa + 1024 + j * 256, T2, j);
        bar_arrive(7, 256);
        TS(7);
      }
      uint4 ga[10];
      uint32_t om[2];
      const uint32_t gb = sb + SM_D + (16 * w + g) * 64 + (((lane ^ (g >> 1)) & 3) << 4);
      uint8_t* go = P.out + (size_t)(rb * 64 + w * 16 + g) * 1280 + cb * 320 + (lane & 3) * 16;
#define LDGA(j) ga[j] = lds128m(gb + ((j) >> 1) * 4096 + ((j) & 1) * 512)
#pragma unroll
      for (int c = EG; c < 24 - LS; c++) {
        if (SPN & 2) mbar_spin(BAR(B_F2 + g2s(c)), g2u(c) & 1); else mbar_wait(BAR(B_F2 + g2s(c)), g2u(c) & 1);
        if (c & 1) TS(36 + (c >> 1));
        WG_FENCE();
#pragma unroll
        for (int kk = 0; kk < 4; kk++) {
          wgmma_ss_tb_n160(acc, dA0 + (g2a(g2s(c)) / 16 + kk * 2), dB0 + (g2b(g2s(c)) / 16 + kk * 64), c > 0 || kk > 0);
          if (kk == PSP || kk == 3) WG_COMMIT();
          if (!GL && kk == PSP && c >= GC && c < GC + 8 / GN) {
            if (c == GC) {
              mbar_wait(BAR(B_PF), 0);
              const float gv0 = __uint_as_float(lds32(sb + SM_GT + (16 * w + g) * 4)), gv1 = __uint_as_float(lds32(sb + SM_GT + (16 * w + g + 8) * 4));
              om[0] = pack_bf16(1.0f - gv0, 1.0f - gv0); om[1] = pack_bf16(1.0f - gv1, 1.0f - gv1);
            }
#pragma unroll
            for (int j = 0; j < GN; j++) LDGA((c - GC) * GN + j);
          }
          if (kk == PSP && c > 0 && c < 19) { WG_WAIT(1); if (lane == 0) mbar_arrive(BAR(B_E2 + g2s(c - 1))); }
        }
      }
#define OUT(j, acc) { const float* a = (acc) + 16 * ((j) >> 1) + 2 * ((j) & 1); \
        stg128(go + ((j) & 1) * 10240 + ((j) >> 1) * 64, badd2(ga[j].x, bmul2(om[(j) & 1], pack_bf16(a[0], a[1]))), badd2(ga[j].y, bmul2(om[(j) & 1], pack_bf16(a[4], a[5]))), \
               badd2(ga[j].z, bmul2(om[(j) & 1], pack_bf16(a[8], a[9]))), badd2(ga[j].w, bmul2(om[(j) & 1], pack_bf16(a[12], a[13])))); }
      constexpr int C0 = 24 - LS;
      static_assert(SW >= 26 && LS <= 5 && GC + 8 / GN <= C0, "");
      float ab[80 - NA / 2];
#define GB(c) { _Pragma("unroll") for (int kk = 0; kk < 4; kk++) MMA_B(ab, dA0 + (g2a(g2s(c)) / 16 + kk * 2), dB0 + (g2b(g2s(c)) / 16 + NA * 8 + kk * 64), c > C0 || kk > 0); }
      mbar_wait(BAR(B_F2 + g2s(C0)), g2u(C0) & 1);
      WG_FENCE();
      GB(C0)
      WG_COMMIT();
      WG_WAIT(1);
#pragma unroll
      for (int c = C0; c < 24; c++) {
        if (c == 23) { TS(11); mbar_wait(BAR(B_GA), 0); }
        if (c > C0) { if (SPN & 2) mbar_spin(BAR(B_F2 + g2s(c)), g2u(c) & 1); else mbar_wait(BAR(B_F2 + g2s(c)), g2u(c) & 1); }
        if (c == 23) {
          if (GL) {
            const float gv0 = __uint_as_float(lds32(sb + SM_GT + (16 * w + g) * 4)), gv1 = __uint_as_float(lds32(sb + SM_GT + (16 * w + g + 8) * 4));
            om[0] = pack_bf16(1.0f - gv0, 1.0f - gv0); om[1] = pack_bf16(1.0f - gv1, 1.0f - gv1);
          }
#pragma unroll
          for (int j = GL ? 0 : 8; j < 10; j++) LDGA(j);
        }
        if (c & 1) TS(36 + (c >> 1));
        WG_FENCE();
#pragma unroll
        for (int kk = 0; kk < 4; kk++) MMA_A(acc, dA0 + (g2a(g2s(c)) / 16 + kk * 2), dB0 + (g2b(g2s(c)) / 16 + kk * 64), 1);
        if (c == C0) {
          WG_COMMIT();
          WG_WAIT(1);
#pragma unroll
          for (int i = 0; i < 80 - NA / 2; i++) fadd_v(ab[i], acc[NA / 2 + i]);
        }
      }
      WG_COMMIT();
      WG_FENCE();
#pragma unroll
      for (int c = C0 + 1; c < C0 + 1 + NB1; c++) GB(c)
      WG_COMMIT();
      TS(21);
      WG_WAIT(1);
      TS(33);
#pragma unroll
      for (int j = 0; j < NA / 16; j++) {
        if (j == E1) {
          TS(22);
          WG_FENCE();
#pragma unroll
          for (int c = C0 + 1 + NB1; c < 24; c++) GB(c)
          WG_COMMIT();
          TS(23);
        }
        OUT(j, acc)
      }
      TS(26);
      WG_WAIT(0);
      TS(12);
#pragma unroll
      for (int j = NA / 16; j < 10; j++) OUT(j, ab - NA / 2)
      TS(13);
    } else {
      {
        float T0[64], T3[16];
        bar_arrive(8, 256);
        WG_FENCE();
#pragma unroll
        for (int s = 0; s < 8; s++) {
          wgmma_rs<128>(T0, (s < 4 ? A0 : A1 - 16) + 4 * s, dX - s, s > 0);
          if (s == 3 || s == 7) WG_COMMIT();
          if (s == RP0) { bar_sync(2, 128); red_ld(v, sb + SM_W + 49152, t128); }
          if (s == RP1) red_st(v, sb + SM_D + 128 + 3 * TP, t128);
          if (s == RP2) { red_fin(BAR(B_ZR + 3)); TS(34); }
        }
        conv_ldA<3072>(A2, ra, zz);
        conv_grp<32, 0>(T3, A2, dX);
        WG_WAIT(2); conv_ldA<3072 + 128>(A0, ra, zz, A2);
        conv_grp<32, 1>(T3, A0, dX);
        const uint32_t pa = sb + SM_W + po + (w >> 1) * 8192;
        bar_sync(7, 256);
        uint4 u[6];
#pragma unroll
        for (int j = 0; j < 6; j++) u[j] = ldsm4t(pa + 1024 + j * 512);
        WG_WAIT(2);
        PST(pa, T0, 0); PST(pa + 512, T0, 2);
#define PSTA(j) stsm4t(pa + (j) * 256, badd2(u[(j) / 2 - 2].x, pack_bf16(T0[4 * (j)], T0[4 * (j) + 1])), badd2(u[(j) / 2 - 2].y, pack_bf16(T0[4 * (j) + 2], T0[4 * (j) + 3])), \
                       badd2(u[(j) / 2 - 2].z, pack_bf16(T0[4 * (j) + 4], T0[4 * (j) + 5])), badd2(u[(j) / 2 - 2].w, pack_bf16(T0[4 * (j) + 6], T0[4 * (j) + 7])))
#pragma unroll
        for (int j = 4; j < 12; j += 2) PSTA(j);
        WG_WAIT(0);
        TS(32);
#pragma unroll
        for (int i = 0; i < 16; i++) T0[48 + i] += T3[i];
        PSTA(12); PSTA(14);
        TS(7);
        bar_sync(2, 128);
        TS(1);
        red_ld(v, sb + SM_W, t128);
        red_st(v, sb + SM_D + 128 + 4 * TP, t128);
        TS(2);
        red_fin(BAR(B_ZR + 4));
      }
      TS(35);
      const uint32_t zo = sb + ((lane & 7) + 8 * (lane >> 4)) * 128 + (((w + ((((lane >> 3) ^ rb) & 1) << 2)) ^ (lane & 7)) << 4);
      mbar_wait(BAR(B_Q), 0);
      mbar_wait(BAR(B_Z), 0);
      TS(10);
      uint4 zr[10], qr[10];
#pragma unroll
      for (int j = 0; j < 10; j++) { if (j < 8) zr[j] = ldsm4t(zo + (j < 2 ? SM_D + 20480 : SM_W - 4096) + j * 2048); qr[j] = ldsm4(sb + SM_D + (j >> 1) * 4096 + (fo ^ ((j & 1) << 5))); }
      const float gv0 = __uint_as_float(lds32(sb + SM_GT + (16 * w + g) * 4)), gv1 = __uint_as_float(lds32(sb + SM_GT + (16 * w + g + 8) * 4));
      const uint32_t g0 = pack_bf16(gv0, gv0), g1 = pack_bf16(gv1, gv1);
#pragma unroll
      for (int j = 0; j < 10; j++) {
        if (j == 8) { if (!GL) mbar_arrive(BAR(B_PF)); TS(12); mbar_wait(BAR(B_Z + 1), 0); TS(11); zr[8] = ldsm4t(zo + SM_W + 6 * 2048); zr[9] = ldsm4t(zo + SM_W + 7 * 2048); }
        stsm4(sb + SM_D + (j >> 1) * 4096 + (fo ^ ((j & 1) << 5)), bmul2(g0, bmul2(qr[j].x, zr[j].x)), bmul2(g1, bmul2(qr[j].y, zr[j].y)), bmul2(g0, bmul2(qr[j].z, zr[j].z)), bmul2(g1, bmul2(qr[j].w, zr[j].w)));
      }
      mbar_arrive(BAR(B_GA));
      TS(13);
    }
  }
}

typedef CUresult (*EncFn)(CUtensorMap*, CUtensorMapDataType, cuuint32_t, void*, const cuuint64_t*, const cuuint64_t*, const cuuint32_t*, const cuuint32_t*,
                          CUtensorMapInterleave, CUtensorMapSwizzle, CUtensorMapL2promotion, CUtensorMapFloatOOBfill);

void enc(EncFn fn, CUtensorMap* m, CUtensorMapDataType dt, int rank, const void* p, const cuuint64_t* gd, const cuuint64_t* gs, const cuuint32_t* bd, CUtensorMapSwizzle sw) {
  cuuint32_t es[5] = {1, 1, 1, 1, 1};
  fn(m, dt, rank, (void*)p, gd, gs, bd, es, CU_TENSOR_MAP_INTERLEAVE_NONE, sw, CU_TENSOR_MAP_L2_PROMOTION_L2_128B, CU_TENSOR_MAP_FLOAT_OOB_FILL_NONE);
}

}

extern "C" void kernel_launch(void* const* d_in, const int* in_sizes, int n_in, void* d_out, int out_size) {
  static EncFn fn = nullptr;
  static void *zp = nullptr, *xp = nullptr;
  if (!fn) {
    cudaGetSymbolAddress(&zp, g_z);
    cudaGetSymbolAddress(&xp, g_X);
    void* f = nullptr; cudaDriverEntryPointQueryResult qr;
    cudaGetDriverEntryPoint("cuTensorMapEncodeTiled", &f, cudaEnableDefault, &qr);
    fn = (EncFn)f;
    cudaFuncSetAttribute(fused_kernel, cudaFuncAttributeMaxDynamicSharedMemorySize, SM_TOTAL);
  }
  Maps m;
  const CUtensorMapDataType BF = CU_TENSOR_MAP_DATA_TYPE_BFLOAT16;
  { cuuint64_t gd[2] = {640, 2048}, gs[1] = {1280}; cuuint32_t bd[2] = {64, 128}; enc(fn, &m.x, BF, 2, d_in[0], gd, gs, bd, CU_TENSOR_MAP_SWIZZLE_128B); }
  { cuuint64_t gd[3] = {64, 640, 24}, gs[2] = {3072, 128}; cuuint32_t bd[3] = {64, 32, 3};
    enc(fn, &m.wg, BF, 3, d_in[7], gd, gs, bd, CU_TENSOR_MAP_SWIZZLE_128B); enc(fn, &m.wu, BF, 3, d_in[8], gd, gs, bd, CU_TENSOR_MAP_SWIZZLE_128B); }
  { cuuint64_t gd[3] = {32, 1536, 20}, gs[2] = {1280, 64}; cuuint32_t bd[3] = {32, 64, 4}; enc(fn, &m.wd, BF, 3, d_in[9], gd, gs, bd, CU_TENSOR_MAP_SWIZZLE_64B); }
  { cuuint64_t gd[3] = {32, 2048, 20}, gs[2] = {1280, 64}; cuuint32_t bk[3] = {32, 35, 2}, bv[3] = {32, 32, 2};
    enc(fn, &m.k, BF, 3, d_in[1], gd, gs, bk, CU_TENSOR_MAP_SWIZZLE_NONE); enc(fn, &m.v, BF, 3, d_in[2], gd, gs, bv, CU_TENSOR_MAP_SWIZZLE_NONE); }
  { cuuint64_t gd[5] = {1024, 16, 2, 2, 485}, gs[4] = {40960, 2048, 20480, 4096}; cuuint32_t bd[5] = {16, 16, 2, 2, 1}; enc(fn, &m.xs, BF, 5, xp, gd, gs, bd, CU_TENSOR_MAP_SWIZZLE_NONE); }
  { cuuint64_t gd[3] = {64, 16, 1280}, gs[2] = {128, 2048}; cuuint32_t bd[3] = {64, 18, 10}; enc(fn, &m.xl, BF, 3, xp, gd, gs, bd, CU_TENSOR_MAP_SWIZZLE_NONE); }
  { cuuint64_t gd[3] = {32, 2048, 20}, gs[2] = {1280, 64}; cuuint32_t bd[3] = {32, 64, 5}, bq[3] = {32, 64, 1};
    enc(fn, &m.q, BF, 3, d_in[0], gd, gs, bq, CU_TENSOR_MAP_SWIZZLE_64B); enc(fn, &m.o, BF, 3, d_out, gd, gs, bd, CU_TENSOR_MAP_SWIZZLE_64B); }
  { cuuint64_t gd[2] = {2048, 640}, gs[1] = {4096}; cuuint32_t bd[2] = {64, 32}; enc(fn, &m.z, BF, 2, zp, gd, gs, bd, CU_TENSOR_MAP_SWIZZLE_128B); }
  Ptrs p;
  p.out = (uint8_t*)d_out; p.x = (const __nv_bfloat16*)d_in[0]; p.shift_k = (const __nv_bfloat16*)d_in[3]; p.ssm_k = (const __nv_bfloat16*)d_in[4];
  p.ssm_D = (const __nv_bfloat16*)d_in[5]; p.gate_w = (const __nv_bfloat16*)d_in[10];
  p.wg = (const __nv_bfloat16*)d_in[7]; p.wu = (const __nv_bfloat16*)d_in[8];
  fused_kernel<<<128, 384, SM_TOTAL, cudaStreamPerThread>>>(m, p, 0u);
}
```

```cpp
#include <cuda_runtime.h>
#include <cuda_bf16.h>
#include <cuda.h>
#include <stdint.h>

namespace {

constexpr int XP = 2304;
constexpr int XCH = 2 * XP;
constexpr int TP = 8320;
#define KV0 3
#define KV1 4
#define KV2 5
#define KV3 6
#define KV4 7
#define NPRE 1
#define PD 10
#define PF0 10
#define LSTEP 0
#define WD_N 99
#define SK_N 9
#define MAP1 1
#define MAP2 4
#define SGB 8
#define HOFF 2
#define PF_N 14
#define X9_N 15
#define SG0 40
#define G2P 2
#define RP0 1
#define RP1 4
#define RP2 7
#define RQ0 1
#define RQ1 3
#define RQ2 6
#define SG1 4

#define RM 2
#define PER 336
#define TICK 1
#define TDEL 0
#define XS 7
#define RS 5
#define EG 1
#define WU 4
#define LS 4
#define E1 2
#define NB1 2
#define GN 4
#define GC (19 - 8 / GN)
#define NA 64
#define MMA_A wgmma_ss_tb_n64
#define MMA_B wgmma_ss_tb_n96
#define WL_N 17
#define GL 1
#define SW 26
#define PF8 17
#define PW 1
#define SHB 1
#define SPN 0
#define PSP 3
#define SG0B SG0
#define SG1B SG1
#define LA 0
#define NB0 0
#define BD 0
#define FI 1
#define XA 99
#define RA RS
#define EF 0
#define RE0 0
#define RE1 2
#define RE2 3
__host__ __device__ constexpr int g2s(int c) { return c < XS ? c % 5 : (c - XS) % 6 == 0 ? 5 : (XS + (c - XS) % 6 - 1) % 5; }
__host__ __device__ constexpr int g2u(int c) { return c < XS ? c / 5 : (c - XS) / 6 + (g2s(c) < 5 ? (XS - g2s(c) + 4) / 5 : 0); }
constexpr uint32_t SM_W = 0;
constexpr uint32_t SM_X = 122880;
constexpr uint32_t SM_R2 = 73728;
constexpr uint32_t SM_D = 188416;
__host__ __device__ constexpr uint32_t g2a(int s) { return s < 4 ? SM_R2 + s * 28672 : s == 4 ? 65536 : SM_D + 24576; }
__host__ __device__ constexpr uint32_t g2b(int s) { return s < 4 ? SM_R2 + s * 28672 + 8192 : s == 4 ? 24576 : 45056; }
__host__ __device__ constexpr int g2i(int c) { return c <= XA ? g2s(c) : c == XA + 1 ? 6 : g2i(c - 7); }
__host__ __device__ constexpr uint32_t g2A(int c) { return g2i(c) == 6 ? 16384 : g2a(g2i(c)); }
__host__ __device__ constexpr uint64_t g2seqa() { uint64_t v = 0; for (int c = 23; c >= 5; c--) v = v * 8 + g2i(c); return v; }
__host__ __device__ constexpr uint64_t g2seq() { uint64_t v = 0; for (int c = 23; c >= 4; c--) v = v * 8 + g2s(c); return v; }
__host__ __device__ constexpr uint32_t g2par() { uint32_t v = 0; for (int c = 23; c >= 4; c--) v = v * 2 + (c == 4 ? 0 : c == XS ? 1 : (g2u(c) - 1) & 1); return v; }
__host__ __device__ constexpr uint64_t g2ta() { uint64_t v = 4; for (int s = 5; s >= 0; s--) v = v * 256 + g2a(s) / 4096; return v; }
__host__ __device__ constexpr uint64_t g2tb() { uint64_t v = 0; for (int s = 5; s >= 0; s--) v = v * 256 + g2b(s) / 4096; return v; }
constexpr uint32_t SM_BAR = 231296;
constexpr uint32_t SM_GAP = 172032;
constexpr uint32_t SM_GT = SM_BAR + 592;
constexpr uint32_t SM_GO = SM_GT + 256;
constexpr uint32_t SM_TOTAL = SM_GO + 64;
enum { B_FX = 0  , B_FW = 3  , B_KV = 8  , B_F2 = 13  , B_WD = 27, B_XI = 19, B_HR = 20, B_HF = 21  , B_Z = 28  , B_WP = 23, B_F9 = 24, B_GF = 25, B_PRE = 26,
       B_EW = 30  , B_EX = 36  , B_G1 = 39, B_E2 = 42  , B_HC = 48, B_Q = 49, B_KD = 50, B_HS = 54  , B_ZR = 60  , B_GA = 65, B_PF = 66   };

__device__ __align__(1024) uint8_t g_X[640 * 4096];
__device__ __align__(1024) uint8_t g_h[2048 * 1536 * 2];
__device__ __align__(1024) uint8_t g_wd[1536 * 640 * 2];
__device__ __align__(1024) uint8_t g_z[640 * 4096];
__device__ __align__(1024) float g_gate[2048];
__device__ uint32_t g_cnt[46 * 32];
#define TS(i)
#define TS1(i)
#define TR(v)
#define TW(i, v)

struct Maps { CUtensorMap x, wg, wu, wd, k, v, q, o, z, xs, xl; };
struct Ptrs { uint8_t* out; const __nv_bfloat16 *x, *shift_k, *ssm_k, *ssm_D, *gate_w, *wg, *wu; };

__device__ __forceinline__ uint32_t clk() { uint32_t t; asm volatile("mov.u32 %0, %%clock;" : "=r"(t) :: "memory"); return t; }
__device__ __forceinline__ uint32_t smem_u32(const void* p) { return (uint32_t)__cvta_generic_to_shared(p); }
__device__ __forceinline__ bool elect_one() { uint32_t p; asm volatile("{.reg .pred P; elect.sync _|P, 0xffffffff; selp.u32 %0, 1, 0, P;}" : "=r"(p)); return p; }
__device__ __forceinline__ void mbar_init(uint32_t bar, uint32_t cnt) { asm volatile("mbarrier.init.shared::cta.b64 [%0], %1;" ::"r"(bar), "r"(cnt)); }
__device__ __forceinline__ void mbar_expect_tx(uint32_t bar, uint32_t bytes) { asm volatile("mbarrier.arrive.expect_tx.shared::cta.b64 _, [%0], %1;" ::"r"(bar), "r"(bytes) : "memory"); }
__device__ __forceinline__ void mbar_arrive(uint32_t bar) { asm volatile("mbarrier.arrive.shared::cta.b64 _, [%0];" ::"r"(bar) : "memory"); }
__device__ __forceinline__ void mbar_wait(uint32_t bar, uint32_t parity) {
  uint32_t ok;
  asm volatile("{.reg .pred p; mbarrier.try_wait.parity.shared::cta.b64 p, [%1], %2; selp.u32 %0,1,0,p;}" : "=r"(ok) : "r"(bar), "r"(parity) : "memory");
  if (!ok) {
    uint32_t it = 0;
    do {
      asm volatile("{.reg .pred p; mbarrier.try_wait.parity.shared::cta.b64 p, [%1], %2, 2000; selp.u32 %0,1,0,p;}" : "=r"(ok) : "r"(bar), "r"(parity) : "memory");
    } while (!ok && ++it < 100000u);
  }
}
__device__ __forceinline__ void mbar_spin(uint32_t bar, uint32_t parity) {
  asm volatile("{.reg .pred p, q; .reg .u32 n; mov.u32 n, 400000;\n"
               "WL%=: mbarrier.try_wait.parity.shared::cta.b64 p, [%0], %1; sub.u32 n, n, 1; setp.ne.and.u32 q, n, 0, !p; @q bra WL%=;}" ::"r"(bar), "r"(parity) : "memory");
}
#define MS 0
template <int B> __device__ __forceinline__ void mbar_w(uint32_t bar, uint32_t parity) { if (MS & B) mbar_spin(bar, parity); else mbar_wait(bar, parity); }
__device__ __forceinline__ void flag_wait(const uint32_t* p, uint32_t target) {
  uint32_t v, it = 0;
  while (true) {
    asm volatile("ld.acquire.gpu.global.u32 %0, [%1];" : "=r"(v) : "l"(p) : "memory");
    if ((int)(v - target) >= 0) break;
    if (++it > 400000u) break;
    __nanosleep(20);
  }
  asm volatile("fence.proxy.async.global;" ::: "memory");
}
__device__ __forceinline__ void flag_add(uint32_t* p, uint32_t v) {
  asm volatile("red.release.gpu.global.add.u32 [%0], %1;" ::"l"(p), "r"(v) : "memory");
}
__device__ __forceinline__ void flag_add_relaxed(uint32_t* p, uint32_t v) {
  asm volatile("red.relaxed.gpu.global.add.u32 [%0], %1;" ::"l"(p), "r"(v) : "memory");
}
__device__ __forceinline__ bool mbar_test(uint32_t bar, uint32_t parity) {
  uint32_t ok;
  asm volatile("{.reg .pred p; mbarrier.test_wait.parity.shared::cta.b64 p, [%1], %2; selp.u32 %0,1,0,p;}" : "=r"(ok) : "r"(bar), "r"(parity) : "memory");
  return ok;
}
__device__ __forceinline__ void cp_async16(uint32_t dst, const void* src) { asm volatile("cp.async.cg.shared.global [%0], [%1], 16;" ::"r"(dst), "l"(src) : "memory"); }
__device__ __forceinline__ void tma2d(uint32_t dst, const CUtensorMap* m, uint32_t bar, int c0, int c1) {
  asm volatile("cp.async.bulk.tensor.2d.shared::cluster.global.mbarrier::complete_tx::bytes [%0], [%1, {%3,%4}], [%2];" ::"r"(dst), "l"(m), "r"(bar), "r"(c0), "r"(c1) : "memory");
}
__device__ __forceinline__ void tma3d(uint32_t dst, const CUtensorMap* m, uint32_t bar, int c0, int c1, int c2) {
  asm volatile("cp.async.bulk.tensor.3d.shared::cluster.global.mbarrier::complete_tx::bytes [%0], [%1, {%3,%4,%5}], [%2];" ::"r"(dst), "l"(m), "r"(bar), "r"(c0), "r"(c1), "r"(c2) : "memory");
}
__device__ __forceinline__ void tma3d_store(const CUtensorMap* m, uint32_t src, int c0, int c1, int c2) {
  asm volatile("cp.async.bulk.tensor.3d.global.shared::cta.bulk_group [%0, {%2,%3,%4}], [%1];" ::"l"(m), "r"(src), "r"(c0), "r"(c1), "r"(c2) : "memory");
}
__device__ __forceinline__ void bulk_g2s(uint32_t dst, const void* src, uint32_t bytes, uint32_t bar) {
  asm volatile("cp.async.bulk.shared::cluster.global.mbarrier::complete_tx::bytes [%0], [%1], %2, [%3];" ::"r"(dst), "l"(src), "r"(bytes), "r"(bar) : "memory");
}
__device__ __forceinline__ void bulk_s2g(void* dst, uint32_t src, uint32_t bytes) {
  asm volatile("cp.async.bulk.global.shared::cta.bulk_group [%0], [%1], %2;" ::"l"(dst), "r"(src), "r"(bytes) : "memory");
}
__device__ __forceinline__ void l2_prefetch(const void* src, uint32_t bytes) {
  asm volatile("cp.async.bulk.prefetch.L2.global [%0], %1;" ::"l"(src), "r"(bytes) : "memory");
}
__device__ __forceinline__ void tma3d_prefetch(const CUtensorMap* m, int c0, int c1, int c2) {
  asm volatile("cp.async.bulk.prefetch.tensor.3d.L2.global.tile [%0, {%1,%2,%3}];" ::"l"(m), "r"(c0), "r"(c1), "r"(c2) : "memory");
}
__device__ __forceinline__ void tmap_prefetch(const CUtensorMap* m) { asm volatile("prefetch.tensormap [%0];" ::"l"(m) : "memory"); }
__device__ __forceinline__ uint64_t mkdesc(uint32_t addr, uint32_t lbo, uint32_t sbo, uint32_t swz) {
  return (uint64_t)((addr & 0x3FFFF) >> 4) | ((uint64_t)(lbo >> 4) << 16) | ((uint64_t)(sbo >> 4) << 32) | ((uint64_t)swz << 62);
}
#define WG_FENCE() asm volatile("wgmma.fence.sync.aligned;" ::: "memory")
#define WG_COMMIT() asm volatile("wgmma.commit_group.sync.aligned;" ::: "memory")
#define WG_WAIT(n) asm volatile("wgmma.wait_group.sync.aligned " #n ";" ::: "memory")
__device__ __forceinline__ void bar_sync(int id, int n) { asm volatile("bar.sync %0, %1;" ::"r"(id), "r"(n) : "memory"); }
__device__ __forceinline__ void bar_arrive(int id, int n) { asm volatile("bar.arrive %0, %1;" ::"r"(id), "r"(n) : "memory"); }
__device__ __forceinline__ uint32_t pack_bf16(float lo, float hi) { uint32_t r; asm("cvt.rn.bf16x2.f32 %0, %1, %2;" : "=r"(r) : "f"(hi), "f"(lo)); return r; }
__device__ __forceinline__ uint32_t bmul2(uint32_t a, uint32_t b) { uint32_t r; asm("mul.rn.bf16x2 %0, %1, %2;" : "=r"(r) : "r"(a), "r"(b)); return r; }
__device__ __forceinline__ uint32_t badd2(uint32_t a, uint32_t b) { uint32_t r; asm("add.rn.bf16x2 %0, %1, %2;" : "=r"(r) : "r"(a), "r"(b)); return r; }
__device__ __forceinline__ uint32_t bfma2(uint32_t a, uint32_t b, uint32_t c) { uint32_t r; asm("fma.rn.bf16x2 %0, %1, %2, %3;" : "=r"(r) : "r"(a), "r"(b), "r"(c)); return r; }
__device__ __forceinline__ uint32_t lds32(uint32_t a) { uint32_t r; asm volatile("ld.shared.u32 %0, [%1];" : "=r"(r) : "r"(a)); return r; }
__device__ __forceinline__ uint32_t lds32v(uint32_t a) { uint32_t r; asm volatile("ld.shared.u32 %0, [%1];" : "=r"(r) : "r"(a) : "memory"); return r; }
__device__ __forceinline__ uint4 lds128(uint32_t a) { uint4 v; asm volatile("ld.shared.v4.u32 {%0,%1,%2,%3}, [%4];" : "=r"(v.x), "=r"(v.y), "=r"(v.z), "=r"(v.w) : "r"(a)); return v; }
__device__ __forceinline__ uint4 lds128m(uint32_t a) { uint4 v; asm volatile("ld.shared.v4.u32 {%0,%1,%2,%3}, [%4];" : "=r"(v.x), "=r"(v.y), "=r"(v.z), "=r"(v.w) : "r"(a) : "memory"); return v; }
__device__ __forceinline__ void sts128(uint32_t a, uint32_t x, uint32_t y, uint32_t z, uint32_t w) { asm volatile("st.shared.v4.u32 [%0], {%1,%2,%3,%4};" ::"r"(a), "r"(x), "r"(y), "r"(z), "r"(w) : "memory"); }
__device__ __forceinline__ void stg128(void* a, uint32_t x, uint32_t y, uint32_t z, uint32_t w) { asm volatile("st.global.v4.u32 [%0], {%1,%2,%3,%4};" ::"l"(a), "r"(x), "r"(y), "r"(z), "r"(w) : "memory"); }
__device__ __forceinline__ void stsm4(uint32_t a, uint32_t x, uint32_t y, uint32_t z, uint32_t w) { asm volatile("stmatrix.sync.aligned.m8n8.x4.shared.b16 [%0], {%1,%2,%3,%4};" ::"r"(a), "r"(x), "r"(y), "r"(z), "r"(w) : "memory"); }
__device__ __forceinline__ void stsm4t(uint32_t a, uint32_t x, uint32_t y, uint32_t z, uint32_t w) { asm volatile("stmatrix.sync.aligned.m8n8.x4.trans.shared.b16 [%0], {%1,%2,%3,%4};" ::"r"(a), "r"(x), "r"(y), "r"(z), "r"(w) : "memory"); }
__device__ __forceinline__ uint4 ldsm4(uint32_t a) { uint4 v; asm volatile("ldmatrix.sync.aligned.m8n8.x4.shared.b16 {%0,%1,%2,%3}, [%4];" : "=r"(v.x), "=r"(v.y), "=r"(v.z), "=r"(v.w) : "r"(a) : "memory"); return v; }
__device__ __forceinline__ uint4 ldsm4t(uint32_t a) { uint4 v; asm volatile("ldmatrix.sync.aligned.m8n8.x4.trans.shared.b16 {%0,%1,%2,%3}, [%4];" : "=r"(v.x), "=r"(v.y), "=r"(v.z), "=r"(v.w) : "r"(a) : "memory"); return v; }
__device__ __forceinline__ void tanh_h(float& a) { asm volatile("{.reg .f32 t; mul.f32 t, %0, 0f3F000000; tanh.approx.f32 %0, t;}" : "+f"(a)); }
__device__ __forceinline__ uint32_t sig_fin(float lo, float hi, float h) {
  uint32_t r;
  asm volatile("{.reg .f32 a, b; fma.rn.f32 a, %1, %3, %3; fma.rn.f32 b, %2, %3, %3; cvt.rn.bf16x2.f32 %0, b, a;}" : "=r"(r) : "f"(lo), "f"(hi), "f"(h));
  return r;
}
template <int LO, int HI> __device__ __forceinline__ uint32_t sig_range(float* a, uint32_t* sg, uint32_t zz) {
  uint32_t dep = 0;
#pragma unroll
  for (int b = LO; b < HI; b += SGB) {
    const int e = b + SGB < HI ? b + SGB : HI;
#pragma unroll
    for (int i = 2 * b; i < 2 * e; i++) tanh_h(a[i]);
    const float h = __uint_as_float(0x3f000000u | (__float_as_uint(a[2 * e - 1]) & zz));
#pragma unroll
    for (int i = b; i < e; i++) { sg[i] = sig_fin(a[2 * i], a[2 * i + 1], h); dep |= sg[i]; }
  }
  return dep & zz;
}
__device__ __forceinline__ void fadd_v(float& a, float b) { asm volatile("add.f32 %0, %0, %1;" : "+f"(a) : "f"(b)); }

__device__ __forceinline__ void wgmma_ss_tb_n192(float* d, uint64_t da, uint64_t db, int sc) {
  asm volatile("{.reg .pred p; setp.ne.b32 p, %98, 0;\n"
   "wgmma.mma_async.sync.aligned.m64n192k16.f32.bf16.bf16 {%0,%1,%2,%3,%4,%5,%6,%7,%8,%9,%10,%11,%12,%13,%14,%15,%16,%17,%18,%19,%20,%21,%22,%23,%24,%25,%26,%27,%28,%29,%30,%31,%32,%33,%34,%35,%36,%37,%38,%39,%40,%41,%42,%43,%44,%45,%46,%47,%48,%49,%50,%51,%52,%53,%54,%55,%56,%57,%58,%59,%60,%61,%62,%63,%64,%65,%66,%67,%68,%69,%70,%71,%72,%73,%74,%75,%76,%77,%78,%79,%80,%81,%82,%83,%84,%85,%86,%87,%88,%89,%90,%91,%92,%93,%94,%95}, %96, %97, p, 1, 1, 0, 1;}\n"
   : "+f"(d[0]),"+f"(d[1]),"+f"(d[2]),"+f"(d[3]),"+f"(d[4]),"+f"(d[5]),"+f"(d[6]),"+f"(d[7]),"+f"(d[8]),"+f"(d[9]),"+f"(d[10]),"+f"(d[11]),"+f"(d[12]),"+f"(d[13]),"+f"(d[14]),"+f"(d[15]),"+f"(d[16]),"+f"(d[17]),"+f"(d[18]),"+f"(d[19]),"+f"(d[20]),"+f"(d[21]),"+f"(d[22]),"+f"(d[23]),"+f"(d[24]),"+f"(d[25]),"+f"(d[26]),"+f"(d[27]),"+f"(d[28]),"+f"(d[29]),"+f"(d[30]),"+f"(d[31]),"+f"(d[32]),"+f"(d[33]),"+f"(d[34]),"+f"(d[35]),"+f"(d[36]),"+f"(d[37]),"+f"(d[38]),"+f"(d[39]),"+f"(d[40]),"+f"(d[41]),"+f"(d[42]),"+f"(d[43]),"+f"(d[44]),"+f"(d[45]),"+f"(d[46]),"+f"(d[47]),"+f"(d[48]),"+f"(d[49]),"+f"(d[50]),"+f"(d[51]),"+f"(d[52]),"+f"(d[53]),"+f"(d[54]),"+f"(d[55]),"+f"(d[56]),"+f"(d[57]),"+f"(d[58]),"+f"(d[59]),"+f"(d[60]),"+f"(d[61]),"+f"(d[62]),"+f"(d[63]),"+f"(d[64]),"+f"(d[65]),"+f"(d[66]),"+f"(d[67]),"+f"(d[68]),"+f"(d[69]),"+f"(d[70]),"+f"(d[71]),"+f"(d[72]),"+f"(d[73]),"+f"(d[74]),"+f"(d[75]),"+f"(d[76]),"+f"(d[77]),"+f"(d[78]),"+f"(d[79]),"+f"(d[80]),"+f"(d[81]),"+f"(d[82]),"+f"(d[83]),"+f"(d[84]),"+f"(d[85]),"+f"(d[86]),"+f"(d[87]),"+f"(d[88]),"+f"(d[89]),"+f"(d[90]),"+f"(d[91]),"+f"(d[92]),"+f"(d[93]),"+f"(d[94]),"+f"(d[95]) : "l"(da), "l"(db), "r"(sc));
}
__device__ __forceinline__ void wgmma_ss_tb_n160(float* d, uint64_t da, uint64_t db, int sc) {
  asm volatile("{.reg .pred p; setp.ne.b32 p, %82, 0;\n"
   "wgmma.mma_async.sync.aligned.m64n160k16.f32.bf16.bf16 {%0,%1,%2,%3,%4,%5,%6,%7,%8,%9,%10,%11,%12,%13,%14,%15,%16,%17,%18,%19,%20,%21,%22,%23,%24,%25,%26,%27,%28,%29,%30,%31,%32,%33,%34,%35,%36,%37,%38,%39,%40,%41,%42,%43,%44,%45,%46,%47,%48,%49,%50,%51,%52,%53,%54,%55,%56,%57,%58,%59,%60,%61,%62,%63,%64,%65,%66,%67,%68,%69,%70,%71,%72,%73,%74,%75,%76,%77,%78,%79}, %80, %81, p, 1, 1, 0, 1;}\n"
   : "+f"(d[0]),"+f"(d[1]),"+f"(d[2]),"+f"(d[3]),"+f"(d[4]),"+f"(d[5]),"+f"(d[6]),"+f"(d[7]),"+f"(d[8]),"+f"(d[9]),"+f"(d[10]),"+f"(d[11]),"+f"(d[12]),"+f"(d[13]),"+f"(d[14]),"+f"(d[15]),"+f"(d[16]),"+f"(d[17]),"+f"(d[18]),"+f"(d[19]),"+f"(d[20]),"+f"(d[21]),"+f"(d[22]),"+f"(d[23]),"+f"(d[24]),"+f"(d[25]),"+f"(d[26]),"+f"(d[27]),"+f"(d[28]),"+f"(d[29]),"+f"(d[30]),"+f"(d[31]),"+f"(d[32]),"+f"(d[33]),"+f"(d[34]),"+f"(d[35]),"+f"(d[36]),"+f"(d[37]),"+f"(d[38]),"+f"(d[39]),"+f"(d[40]),"+f"(d[41]),"+f"(d[42]),"+f"(d[43]),"+f"(d[44]),"+f"(d[45]),"+f"(d[46]),"+f"(d[47]),"+f"(d[48]),"+f"(d[49]),"+f"(d[50]),"+f"(d[51]),"+f"(d[52]),"+f"(d[53]),"+f"(d[54]),"+f"(d[55]),"+f"(d[56]),"+f"(d[57]),"+f"(d[58]),"+f"(d[59]),"+f"(d[60]),"+f"(d[61]),"+f"(d[62]),"+f"(d[63]),"+f"(d[64]),"+f"(d[65]),"+f"(d[66]),"+f"(d[67]),"+f"(d[68]),"+f"(d[69]),"+f"(d[70]),"+f"(d[71]),"+f"(d[72]),"+f"(d[73]),"+f"(d[74]),"+f"(d[75]),"+f"(d[76]),"+f"(d[77]),"+f"(d[78]),"+f"(d[79]) : "l"(da), "l"(db), "r"(sc));
}
__device__ __forceinline__ void wgmma_ss_tb_n96(float* d, uint64_t da, uint64_t db, int sc) {
  asm volatile("{.reg .pred p; setp.ne.b32 p, %50, 0;\n"
   "wgmma.mma_async.sync.aligned.m64n96k16.f32.bf16.bf16 {%0,%1,%2,%3,%4,%5,%6,%7,%8,%9,%10,%11,%12,%13,%14,%15,%16,%17,%18,%19,%20,%21,%22,%23,%24,%25,%26,%27,%28,%29,%30,%31,%32,%33,%34,%35,%36,%37,%38,%39,%40,%41,%42,%43,%44,%45,%46,%47}, %48, %49, p, 1, 1, 0, 1;}\n"
   : "+f"(d[0]),"+f"(d[1]),"+f"(d[2]),"+f"(d[3]),"+f"(d[4]),"+f"(d[5]),"+f"(d[6]),"+f"(d[7]),"+f"(d[8]),"+f"(d[9]),"+f"(d[10]),"+f"(d[11]),"+f"(d[12]),"+f"(d[13]),"+f"(d[14]),"+f"(d[15]),"+f"(d[16]),"+f"(d[17]),"+f"(d[18]),"+f"(d[19]),"+f"(d[20]),"+f"(d[21]),"+f"(d[22]),"+f"(d[23]),"+f"(d[24]),"+f"(d[25]),"+f"(d[26]),"+f"(d[27]),"+f"(d[28]),"+f"(d[29]),"+f"(d[30]),"+f"(d[31]),"+f"(d[32]),"+f"(d[33]),"+f"(d[34]),"+f"(d[35]),"+f"(d[36]),"+f"(d[37]),"+f"(d[38]),"+f"(d[39]),"+f"(d[40]),"+f"(d[41]),"+f"(d[42]),"+f"(d[43]),"+f"(d[44]),"+f"(d[45]),"+f"(d[46]),"+f"(d[47]) : "l"(da), "l"(db), "r"(sc));
}
__device__ __forceinline__ void wgmma_ss_tb_n64(float* d, uint64_t da, uint64_t db, int sc) {
  asm volatile("{.reg .pred p; setp.ne.b32 p, %34, 0;\n"
   "wgmma.mma_async.sync.aligned.m64n64k16.f32.bf16.bf16 {%0,%1,%2,%3,%4,%5,%6,%7,%8,%9,%10,%11,%12,%13,%14,%15,%16,%17,%18,%19,%20,%21,%22,%23,%24,%25,%26,%27,%28,%29,%30,%31}, %32, %33, p, 1, 1, 0, 1;}\n"
   : "+f"(d[0]),"+f"(d[1]),"+f"(d[2]),"+f"(d[3]),"+f"(d[4]),"+f"(d[5]),"+f"(d[6]),"+f"(d[7]),"+f"(d[8]),"+f"(d[9]),"+f"(d[10]),"+f"(d[11]),"+f"(d[12]),"+f"(d[13]),"+f"(d[14]),"+f"(d[15]),"+f"(d[16]),"+f"(d[17]),"+f"(d[18]),"+f"(d[19]),"+f"(d[20]),"+f"(d[21]),"+f"(d[22]),"+f"(d[23]),"+f"(d[24]),"+f"(d[25]),"+f"(d[26]),"+f"(d[27]),"+f"(d[28]),"+f"(d[29]),"+f"(d[30]),"+f"(d[31]) : "l"(da), "l"(db), "r"(sc));
}
__device__ __forceinline__ void wgmma_rs_tb_n192(float* d, const uint4& a, uint64_t db, int sc) {
  asm volatile("{.reg .pred p; setp.ne.b32 p, %101, 0;\n"
   "wgmma.mma_async.sync.aligned.m64n192k16.f32.bf16.bf16 {%0,%1,%2,%3,%4,%5,%6,%7,%8,%9,%10,%11,%12,%13,%14,%15,%16,%17,%18,%19,%20,%21,%22,%23,%24,%25,%26,%27,%28,%29,%30,%31,%32,%33,%34,%35,%36,%37,%38,%39,%40,%41,%42,%43,%44,%45,%46,%47,%48,%49,%50,%51,%52,%53,%54,%55,%56,%57,%58,%59,%60,%61,%62,%63,%64,%65,%66,%67,%68,%69,%70,%71,%72,%73,%74,%75,%76,%77,%78,%79,%80,%81,%82,%83,%84,%85,%86,%87,%88,%89,%90,%91,%92,%93,%94,%95}, {%96,%97,%98,%99}, %100, p, 1, 1, 1;}\n"
   : "+f"(d[0]),"+f"(d[1]),"+f"(d[2]),"+f"(d[3]),"+f"(d[4]),"+f"(d[5]),"+f"(d[6]),"+f"(d[7]),"+f"(d[8]),"+f"(d[9]),"+f"(d[10]),"+f"(d[11]),"+f"(d[12]),"+f"(d[13]),"+f"(d[14]),"+f"(d[15]),"+f"(d[16]),"+f"(d[17]),"+f"(d[18]),"+f"(d[19]),"+f"(d[20]),"+f"(d[21]),"+f"(d[22]),"+f"(d[23]),"+f"(d[24]),"+f"(d[25]),"+f"(d[26]),"+f"(d[27]),"+f"(d[28]),"+f"(d[29]),"+f"(d[30]),"+f"(d[31]),"+f"(d[32]),"+f"(d[33]),"+f"(d[34]),"+f"(d[35]),"+f"(d[36]),"+f"(d[37]),"+f"(d[38]),"+f"(d[39]),"+f"(d[40]),"+f"(d[41]),"+f"(d[42]),"+f"(d[43]),"+f"(d[44]),"+f"(d[45]),"+f"(d[46]),"+f"(d[47]),"+f"(d[48]),"+f"(d[49]),"+f"(d[50]),"+f"(d[51]),"+f"(d[52]),"+f"(d[53]),"+f"(d[54]),"+f"(d[55]),"+f"(d[56]),"+f"(d[57]),"+f"(d[58]),"+f"(d[59]),"+f"(d[60]),"+f"(d[61]),"+f"(d[62]),"+f"(d[63]),"+f"(d[64]),"+f"(d[65]),"+f"(d[66]),"+f"(d[67]),"+f"(d[68]),"+f"(d[69]),"+f"(d[70]),"+f"(d[71]),"+f"(d[72]),"+f"(d[73]),"+f"(d[74]),"+f"(d[75]),"+f"(d[76]),"+f"(d[77]),"+f"(d[78]),"+f"(d[79]),"+f"(d[80]),"+f"(d[81]),"+f"(d[82]),"+f"(d[83]),"+f"(d[84]),"+f"(d[85]),"+f"(d[86]),"+f"(d[87]),"+f"(d[88]),"+f"(d[89]),"+f"(d[90]),"+f"(d[91]),"+f"(d[92]),"+f"(d[93]),"+f"(d[94]),"+f"(d[95]) : "r"(a.x), "r"(a.y), "r"(a.z), "r"(a.w), "l"(db), "r"(sc));
}
template<int N> __device__ __forceinline__ void wgmma_rs(float* d, const uint32_t* a, uint64_t db, int sc);
template<> __device__ __forceinline__ void wgmma_rs<128>(float* d, const uint32_t* a, uint64_t db, int sc) {
  asm volatile("{.reg .pred p; setp.ne.b32 p, %69, 0;\n"
   "wgmma.mma_async.sync.aligned.m64n128k16.f32.bf16.bf16 {%0,%1,%2,%3,%4,%5,%6,%7,%8,%9,%10,%11,%12,%13,%14,%15,%16,%17,%18,%19,%20,%21,%22,%23,%24,%25,%26,%27,%28,%29,%30,%31,%32,%33,%34,%35,%36,%37,%38,%39,%40,%41,%42,%43,%44,%45,%46,%47,%48,%49,%50,%51,%52,%53,%54,%55,%56,%57,%58,%59,%60,%61,%62,%63}, {%64,%65,%66,%67}, %68, p, 1, 1, 0;}\n"
   : "+f"(d[0]),"+f"(d[1]),"+f"(d[2]),"+f"(d[3]),"+f"(d[4]),"+f"(d[5]),"+f"(d[6]),"+f"(d[7]),"+f"(d[8]),"+f"(d[9]),"+f"(d[10]),"+f"(d[11]),"+f"(d[12]),"+f"(d[13]),"+f"(d[14]),"+f"(d[15]),"+f"(d[16]),"+f"(d[17]),"+f"(d[18]),"+f"(d[19]),"+f"(d[20]),"+f"(d[21]),"+f"(d[22]),"+f"(d[23]),"+f"(d[24]),"+f"(d[25]),"+f"(d[26]),"+f"(d[27]),"+f"(d[28]),"+f"(d[29]),"+f"(d[30]),"+f"(d[31]),"+f"(d[32]),"+f"(d[33]),"+f"(d[34]),"+f"(d[35]),"+f"(d[36]),"+f"(d[37]),"+f"(d[38]),"+f"(d[39]),"+f"(d[40]),"+f"(d[41]),"+f"(d[42]),"+f"(d[43]),"+f"(d[44]),"+f"(d[45]),"+f"(d[46]),"+f"(d[47]),"+f"(d[48]),"+f"(d[49]),"+f"(d[50]),"+f"(d[51]),"+f"(d[52]),"+f"(d[53]),"+f"(d[54]),"+f"(d[55]),"+f"(d[56]),"+f"(d[57]),"+f"(d[58]),"+f"(d[59]),"+f"(d[60]),"+f"(d[61]),"+f"(d[62]),"+f"(d[63]) : "r"(a[0]), "r"(a[1]), "r"(a[2]), "r"(a[3]), "l"(db), "r"(sc));
}
template<> __device__ __forceinline__ void wgmma_rs<96>(float* d, const uint32_t* a, uint64_t db, int sc) {
  asm volatile("{.reg .pred p; setp.ne.b32 p, %53, 0;\n"
   "wgmma.mma_async.sync.aligned.m64n96k16.f32.bf16.bf16 {%0,%1,%2,%3,%4,%5,%6,%7,%8,%9,%10,%11,%12,%13,%14,%15,%16,%17,%18,%19,%20,%21,%22,%23,%24,%25,%26,%27,%28,%29,%30,%31,%32,%33,%34,%35,%36,%37,%38,%39,%40,%41,%42,%43,%44,%45,%46,%47}, {%48,%49,%50,%51}, %52, p, 1, 1, 0;}\n"
   : "+f"(d[0]),"+f"(d[1]),"+f"(d[2]),"+f"(d[3]),"+f"(d[4]),"+f"(d[5]),"+f"(d[6]),"+f"(d[7]),"+f"(d[8]),"+f"(d[9]),"+f"(d[10]),"+f"(d[11]),"+f"(d[12]),"+f"(d[13]),"+f"(d[14]),"+f"(d[15]),"+f"(d[16]),"+f"(d[17]),"+f"(d[18]),"+f"(d[19]),"+f"(d[20]),"+f"(d[21]),"+f"(d[22]),"+f"(d[23]),"+f"(d[24]),"+f"(d[25]),"+f"(d[26]),"+f"(d[27]),"+f"(d[28]),"+f"(d[29]),"+f"(d[30]),"+f"(d[31]),"+f"(d[32]),"+f"(d[33]),"+f"(d[34]),"+f"(d[35]),"+f"(d[36]),"+f"(d[37]),"+f"(d[38]),"+f"(d[39]),"+f"(d[40]),"+f"(d[41]),"+f"(d[42]),"+f"(d[43]),"+f"(d[44]),"+f"(d[45]),"+f"(d[46]),"+f"(d[47]) : "r"(a[0]), "r"(a[1]), "r"(a[2]), "r"(a[3]), "l"(db), "r"(sc));
}
template<> __device__ __forceinline__ void wgmma_rs<64>(float* d, const uint32_t* a, uint64_t db, int sc) {
  asm volatile("{.reg .pred p; setp.ne.b32 p, %37, 0;\n"
   "wgmma.mma_async.sync.aligned.m64n64k16.f32.bf16.bf16 {%0,%1,%2,%3,%4,%5,%6,%7,%8,%9,%10,%11,%12,%13,%14,%15,%16,%17,%18,%19,%20,%21,%22,%23,%24,%25,%26,%27,%28,%29,%30,%31}, {%32,%33,%34,%35}, %36, p, 1, 1, 0;}\n"
   : "+f"(d[0]),"+f"(d[1]),"+f"(d[2]),"+f"(d[3]),"+f"(d[4]),"+f"(d[5]),"+f"(d[6]),"+f"(d[7]),"+f"(d[8]),"+f"(d[9]),"+f"(d[10]),"+f"(d[11]),"+f"(d[12]),"+f"(d[13]),"+f"(d[14]),"+f"(d[15]),"+f"(d[16]),"+f"(d[17]),"+f"(d[18]),"+f"(d[19]),"+f"(d[20]),"+f"(d[21]),"+f"(d[22]),"+f"(d[23]),"+f"(d[24]),"+f"(d[25]),"+f"(d[26]),"+f"(d[27]),"+f"(d[28]),"+f"(d[29]),"+f"(d[30]),"+f"(d[31]) : "r"(a[0]), "r"(a[1]), "r"(a[2]), "r"(a[3]), "l"(db), "r"(sc));
}
template<> __device__ __forceinline__ void wgmma_rs<32>(float* d, const uint32_t* a, uint64_t db, int sc) {
  asm volatile("{.reg .pred p; setp.ne.b32 p, %21, 0;\n"
   "wgmma.mma_async.sync.aligned.m64n32k16.f32.bf16.bf16 {%0,%1,%2,%3,%4,%5,%6,%7,%8,%9,%10,%11,%12,%13,%14,%15}, {%16,%17,%18,%19}, %20, p, 1, 1, 0;}\n"
   : "+f"(d[0]),"+f"(d[1]),"+f"(d[2]),"+f"(d[3]),"+f"(d[4]),"+f"(d[5]),"+f"(d[6]),"+f"(d[7]),"+f"(d[8]),"+f"(d[9]),"+f"(d[10]),"+f"(d[11]),"+f"(d[12]),"+f"(d[13]),"+f"(d[14]),"+f"(d[15]) : "r"(a[0]), "r"(a[1]), "r"(a[2]), "r"(a[3]), "l"(db), "r"(sc));
}

__device__ __forceinline__ void conv_dupA(uint32_t* A, uint32_t zz) {
#pragma unroll
  for (int s = 0; s < 4; s++) {
    asm volatile("xor.b32 %0, %1, %2;" : "=r"(A[4 * s + 3]) : "r"(A[4 * s]), "r"(zz));
    if (s < 3) asm volatile("xor.b32 %0, %1, %2;" : "=r"(A[4 * s + 6]) : "r"(A[4 * s + 1]), "r"(zz));
  }
}
template <int OFF, int DUP = 1> __device__ __forceinline__ void conv_ldA(uint32_t* A, uint32_t ra, uint32_t zz, const uint32_t* Pv = nullptr) {
  if (!SHB || !(OFF & 128)) A[2] = lds32(ra + OFF);
  else if (DUP) asm volatile("xor.b32 %0, %1, %2;" : "=r"(A[2]) : "r"(Pv[13]), "r"(zz));
#pragma unroll
  for (int s = 0; s < 4; s++) { A[4 * s] = lds32(ra + OFF + 32 * s + 16); A[4 * s + 1] = lds32(ra + OFF + 32 * s + 32); }
  if (DUP) conv_dupA(A, zz);
}
template <int N, int H, int ACC = 0> __device__ __forceinline__ void conv_grp(float* T, const uint32_t* A, uint64_t dX) {
  WG_FENCE();
#pragma unroll
  for (int s = 0; s < 4; s++) wgmma_rs<N>(T, A + 4 * s, dX - (4 * H + s), (ACC || H > 0 || s > 0));
  WG_COMMIT();
}
template <int H> __device__ __forceinline__ void conv_grp2(float* T, float* U, const uint32_t* A, uint64_t dX) {
  WG_FENCE();
#pragma unroll
  for (int s = 0; s < 4; s++) {
    wgmma_rs<64>(T, A + 4 * s, dX + 32 - (4 * H + s), (H > 0 || s > 0));
    wgmma_rs<32>(U, A + 4 * s, dX - (4 * H + s), (H > 0 || s > 0));
  }
  WG_COMMIT();
}

__device__ __forceinline__ void red_ld(uint4 (*v)[4], uint32_t pb, int idx) {
#pragma unroll
  for (int n = 0; n < 2; n++)
#pragma unroll
    for (int q = 0; q < 4; q++) { v[n][q] = make_uint4(0, 0, 0, 0); if (n > 0 || idx >= 16 * q) v[n][q] = lds128(pb + idx * 16 + q * 3840 + n * 2048); }
}
__device__ __forceinline__ void red_st(const uint4 (*v)[4], uint32_t zo, int idx) {
#pragma unroll
  for (int m = 0; m < 2; m++)
    sts128(zo + idx * 16 + m * 2048, badd2(badd2(v[m][0].x, v[m][1].x), badd2(v[m][2].x, v[m][3].x)), badd2(badd2(v[m][0].y, v[m][1].y), badd2(v[m][2].y, v[m][3].y)),
           badd2(badd2(v[m][0].z, v[m][1].z), badd2(v[m][2].z, v[m][3].z)), badd2(badd2(v[m][0].w, v[m][1].w), badd2(v[m][2].w, v[m][3].w)));
}
__device__ __forceinline__ void red_fin(uint32_t bar) {
  asm volatile("fence.proxy.async.shared::cta;" ::: "memory");
  mbar_arrive(bar);
}

__global__ void __launch_bounds__(384, 1) fused_kernel(const __grid_constant__ Maps maps, const Ptrs P, const uint32_t zz) {
  extern __shared__ __align__(1024) uint8_t smem[];
  constexpr uint32_t sb = 1024;
  const int tid = threadIdx.x;
  const int b = blockIdx.x;
  const uint32_t bars = sb + SM_BAR;

#define BAR(i) (bars + 8u * (i))
  TR(t63);
  const int rt = (b >> 1) & 15, ct = (b & 1) | ((b >> 5) << 1);
  const int rb = (b & ((1 << (MAP2 - 2)) - 1)) | (((b & 63) >> (MAP2 - 1)) << (MAP2 - 2)), cb = ((b >> (MAP2 - 2)) & 1) | ((b >> 6) << 1);
  const int b2 = cb * 32 + rb;
  const int ch0 = cb * 160 + rb;

  if ((tid >> 5) == 8) {
    if (elect_one()) {
      mbar_init(BAR(B_FX), 1); mbar_init(BAR(B_FW), 1);
      if (FI == 0) { mbar_init(BAR(B_FW + 1), 1); asm volatile("fence.proxy.async.shared::cta;" ::: "memory"); }
      if (FI && NPRE > 1) mbar_init(BAR(B_FW + 1), 1);
      if (FI == 1) asm volatile("fence.mbarrier_init.release.cluster;" ::: "memory");
      mbar_expect_tx(BAR(B_FX), 16384); tma2d(sb + SM_X, &maps.x, BAR(B_FX), 0, rt * 128);
#pragma unroll
      for (int n = 0; n < NPRE; n++) {
        mbar_expect_tx(BAR(B_FW + n), 24576);
        tma3d(sb + SM_W + n * 24576, &maps.wg, BAR(B_FW + n), 0, n * 32, ct * 3); tma3d(sb + SM_W + n * 24576 + 12288, &maps.wu, BAR(B_FW + n), 0, n * 32, ct * 3);
      }
      if (FI && NPRE == 1) mbar_init(BAR(B_FW + 1), 1);
      mbar_init(BAR(B_FX + 1), 1); mbar_init(BAR(B_FX + 2), 1); mbar_init(BAR(B_FW + 2), 1);
      asm volatile("fence.proxy.async.shared::cta;" ::: "memory");
    }
  }
  const int wg = __shfl_sync(0xffffffffu, tid >> 7, 0);

  if (wg == 2) {
    asm volatile("setmaxnreg.dec.sync.aligned.u32 40;");
    bar_sync(0, 384);
    const int warp = __shfl_sync(0xffffffffu, tid >> 5, 0) - 8, lane = tid & 31;
    if (warp == 0) {
      if (elect_one()) {

#pragma unroll
        for (int n = NPRE; n < 20; n++) {
          const int k = n < 14 ? (n >> 1) : n < 17 ? n - 7 : n - 10;
          const bool up = n < 14 ? (n & 1) : (n >= 17);
          if (n == PF_N) { tma3d_prefetch(&maps.wu, 0, 576, ct * 3); tma3d_prefetch(&maps.wu, 0, 608, ct * 3); }
          if (n == PF8) { tma3d_prefetch(&maps.wu, 0, 512, ct * 3); tma3d_prefetch(&maps.wu, 0, 544, ct * 3); }
          if (!up && n != 16) {
            const int xs = k % 3;
            if (k >= 3) mbar_w<8>(BAR(B_EX + xs), ((k / 3) - 1) & 1);
            mbar_expect_tx(BAR(B_FX + xs), 16384);
            tma2d(sb + SM_X + xs * 16384, &maps.x, BAR(B_FX + xs), k * 64, rt * 128);
          }
          const int s = n % 5;
          if (n >= 5) mbar_w<8>(BAR(B_EW + s), ((n / 5) - 1) & 1);
          mbar_expect_tx(BAR(B_FW + s), 24576);
          tma3d(sb + SM_W + s * 24576, n >= 17 ? &maps.wu : &maps.wg, BAR(B_FW + s), 0, n < 14 ? n * 32 : k * 64, ct * 3);
          tma3d(sb + SM_W + s * 24576 + 12288, n < 14 || n >= 17 ? &maps.wu : &maps.wg, BAR(B_FW + s), 0, n < 14 ? n * 32 : k * 64 + 32, ct * 3);
          if (n == X9_N) {
            mbar_expect_tx(BAR(B_F9), 16384);
            tma2d(sb + SM_GAP, &maps.x, BAR(B_F9), 576, rt * 128);
          }
          if (n == KV0 || n == KV1 || n == KV2 || n == KV3 || n == KV4) {
            const int r = n == KV0 ? 0 : n == KV1 ? 1 : n == KV2 ? 2 : n == KV3 ? 3 : 4;
            mbar_expect_tx(BAR(B_KV + r), 8576);
            tma3d(sb + SM_D + r * 8576, &maps.k, BAR(B_KV + r), 0, (b >> 1) * 32 - 3, (b & 1) * 10 + 2 * r);
            tma3d(sb + SM_D + r * 8576 + 4480, &maps.v, BAR(B_KV + r), 0, (b >> 1) * 32, (b & 1) * 10 + 2 * r);
          }
          if (n >= SK_N && n < SK_N + 5) l2_prefetch(P.ssm_k + (size_t)(ch0 + 32 * (n - SK_N)) * 2048, 4096);
          if (n == WD_N && b < 120) tma3d_prefetch(&maps.wd, 0, (b / 5) * 64, (b % 5) * 4);
          if (n == WL_N) {
            mbar_w<8>(BAR(B_EX), 0);
            mbar_expect_tx(BAR(B_WD), b < 120 ? 16384 : 0);
            if (b < 120) tma3d(sb + SM_X, &maps.wd, BAR(B_WD), 0, (b / 5) * 64, (b % 5) * 4);
          }
        }
        TS1(32);
        mbar_wait(BAR(B_PRE), 0);
        const uint32_t target = lds32v(sb + SM_BAR + 576);
        mbar_wait(BAR(B_EW + 0), 1);
        flag_wait(&g_cnt[0], target);
        mbar_expect_tx(BAR(B_XI), 5 * XCH);
        tma3d(sb + SM_W, &maps.xl, BAR(B_XI), 0, -2, b2 * 10);
        TS1(1);
        const uint8_t* wsrc = g_wd + cb * 20480;
        flag_wait(&g_cnt[45 * 32], target);
        TS1(33);
        mbar_wait(BAR(B_G1), 0);
        for (int s = 0; s < 4; s++) {
          mbar_expect_tx(BAR(B_F2 + s), 28672);
          bulk_g2s(sb + SM_R2 + s * 28672 + 8192, wsrc + s * 81920, 20480, BAR(B_F2 + s));
        }
        TS1(2);
        flag_wait(&g_cnt[(1 + rb) * 32], target);
        TS1(3);
        const uint8_t* hsrc = g_h + (size_t)rb * 24 * 8192;
        for (int s = 0; s < 4; s++) {
          if (!(s & 1)) mbar_wait(BAR(B_KV + (s >> 1)), 1);
          bulk_g2s(sb + SM_R2 + s * 28672, hsrc + s * 8192, 8192, BAR(B_F2 + s));
        }
        mbar_expect_tx(BAR(B_Q), 256);
        bulk_g2s(sb + SM_GT, g_gate + rb * 64, 256, BAR(B_Q));
        tmap_prefetch(&maps.z);
        {
          uint32_t tick = 0, par = g2par();
          uint64_t seq = g2seq(), seqa = g2seqa();
          static_assert(XA > XS && XA >= RS, "");
          int cc = 4;
          mbar_wait(BAR(B_HF + 1), 0);
#pragma unroll 1
          for (int c = 4; c < 24; c++) {
            const uint32_t s8 = ((uint32_t)seq & 7) * 8;
            const uint32_t da = sb + ((uint32_t)(g2ta() >> s8) & 0xff) * 4096, db = sb + ((uint32_t)(g2tb() >> s8) & 0xff) * 4096;
            const uint32_t wb = c == 4 ? BAR(B_ZR + 2) : c == XS ? BAR(B_KV + 3) : BAR(B_E2) + s8;
            if (c <= RA || c == RS) {
              mbar_wait(wb, par & 1);
              const uint32_t t = clk(), q = (t + TDEL) / PER + TICK;
              tick = c >= RA ? q * PER : t;
              cc = c == RS ? RS + q % (24 - RS) : c == RA ? RA + q % (RS - RA + (RS == RA)) : c;
            }
            const uint8_t* pa = hsrc + cc * 8192;
            const uint8_t* pw = wsrc + cc * 81920;
            for (int it = 0; (int)(clk() - tick) < 0 && it < 200; it++) {}
            tick += PER;
            if (SPN & 1) mbar_spin(wb, par & 1); else mbar_wait(wb, par & 1);
            bulk_g2s(db, pw, 20480, BAR(B_F2) + s8);
            if (c <= XA) bulk_g2s(da, pa, 8192, BAR(B_F2) + s8);
            mbar_expect_tx(BAR(B_F2) + s8, 28672);
            if (++cc == 24) cc = RS; else if (RA < RS && cc == RS) cc = RA;
            seq >>= 3; par >>= 1;
            if (XA < 23 && c >= XA && c < 23) {
              if (c == XA) mbar_wait(BAR(B_GF), 0);
              bulk_g2s(sb + ((uint32_t)(g2ta() >> (((uint32_t)seqa & 7) * 8)) & 0xff) * 4096, hsrc + cc * 8192, 8192, BAR(B_F2) + ((uint32_t)seq & 7) * 8);
            }
            seqa >>= 3;
          }
        }
        TS1(4);
      }
    } else {
      const int hw = warp - 1;
      if (hw == 2) {
        if (smem_u32(smem) != sb) asm volatile("trap;");
        const int c8 = lane & 7, r4 = lane >> 3;
        float acc[4] = {0.f, 0.f, 0.f, 0.f};
        uint4 gw = __ldg((const uint4*)(P.gate_w + c8 * 8));
        gw.x |= __ldg((const uint32_t*)(P.gate_w + 128 + lane * 16)) & zz;
        uint32_t xs = 0, xph = 0;
        const __nv_bfloat16* pw = (lane & 1 ? P.wu : P.wg) + (rt * 4 + (lane >> 3)) * 1536 + ct * 192 + ((lane >> 1) & 3) * 64;
        const __nv_bfloat16* px = P.x + (rt * 128 + ct * 16 + (lane & 15)) * 640;
        const bool pfw = (lane & 6) != 6;
#define PFK(kk) { if (pfw) asm volatile("prefetch.global.L2 [%0];" ::"l"(pw + (kk) * 98304)); if (lane < 16) asm volatile("prefetch.global.L2 [%0];" ::"l"(px + (kk) * 64)); }
        for (int k = PF0; k < PD; k++) PFK(k)
#pragma unroll 1
        for (int k = 0; k < 10; k++) {
          const uint4 gn = __ldg((const uint4*)(P.gate_w + (k < 9 ? k + 1 : 0) * 64 + c8 * 8));
          if (k == 9) { xs = 3; mbar_wait(BAR(B_F9), 0); } else mbar_wait(BAR(B_FX + xs), xph);
          if (k + PD < 10) PFK(k + PD)
#pragma unroll
          for (int i = 0; i < 4; i++) {
            const int row = (i >> 1) * 64 + ct * 8 + (i & 1) * 4 + r4;
            const uint4 v = lds128(sb + SM_X + xs * 16384 + row * 128 + ((c8 ^ (row & 7)) << 4));
            const uint32_t p[4] = {bmul2(v.x, gw.x), bmul2(v.y, gw.y), bmul2(v.z, gw.z), bmul2(v.w, gw.w)};
#pragma unroll
            for (int e = 0; e < 4; e++) acc[i] += __uint_as_float(p[e] << 16) + __uint_as_float(p[e] & 0xffff0000u);
          }
          __syncwarp();
          if (lane == 0 && k < 7) mbar_arrive(BAR(B_EX + xs));
          __syncwarp();
          if (++xs == 3) { xs = 0; xph ^= 1; }
          gw = gn;
        }
#pragma unroll
        for (int i = 0; i < 4; i++)
#pragma unroll
          for (int o = 1; o < 8; o <<= 1) acc[i] += __shfl_xor_sync(0xffffffffu, acc[i], o);
        if (c8 < 4) {
          const float sv = c8 == 0 ? acc[0] : c8 == 1 ? acc[1] : c8 == 2 ? acc[2] : acc[3];
          const float l = __bfloat162float(__float2bfloat16_rn(sv));
          const float gv = __bfloat162float(__float2bfloat16_rn(1.0f / (1.0f + __expf(-l))));
          asm volatile("st.shared.f32 [%0], %1;" ::"r"(sb + SM_GO + c8 * 16 + r4 * 4), "f"(gv) : "memory");
          asm volatile("fence.proxy.async.shared::cta;" ::: "memory");
        }
        __syncwarp();
        if (lane == 0) { mbar_arrive(BAR(B_G1)); mbar_arrive(BAR(B_HS + 0)); mbar_arrive(BAR(B_HS + 1)); TS1(7); }
      } else {
        const int ht = tid - 288;
        const int rc = b >> 1, chb = (b & 1) * 320;
        const int cl = hw * 32 + (lane >> 1) * 2;
        const __nv_bfloat16* skp = P.shift_k + (chb + cl) * 4;
        uint4 sk = __ldg((const uint4*)skp);
        if (ht < 20) asm volatile("prefetch.global.L2 [%0];" ::"l"(P.shift_k + chb * 4 + ht * 64));
        uint32_t ka = sb + SM_D + hw * 2240 + (lane >> 1) * 4 + (lane & 1) * 1024;
        const uint32_t vo = 4480 - hw * 192, so = 4480 - hw * 192 + (lane >> 1) * 28 - (lane & 1) * 1008;
#pragma unroll 1
        for (int pg = 0; pg < 5; pg++) {
          const uint32_t w0 = __byte_perm(sk.x, sk.z, 0x5410), w1 = __byte_perm(sk.x, sk.z, 0x7632);
          const uint32_t w2 = __byte_perm(sk.y, sk.w, 0x5410), w3 = __byte_perm(sk.y, sk.w, 0x7632);
          sk = __ldg((const uint4*)(skp + (pg < 4 ? pg + 1 : 0) * 256));
          mbar_wait(BAR(B_KV + pg), 0);
          if (ht == 0) TS1(21 + pg);
          uint32_t kk[19], o[8];
#pragma unroll
          for (int i = 0; i < 11; i++) kk[i] = lds32(ka + i * 64);
#pragma unroll
          for (int h = 0; h < 2; h++) {
#pragma unroll
            for (int i = 0; i < 8; i++) o[i] = lds32(ka + vo + (8 * h + i) * 64);
#pragma unroll
            for (int i = 0; i < 8; i++) o[i] = bmul2(bfma2(kk[8 * h + i + 3], w0, bfma2(kk[8 * h + i + 2], w1, bfma2(kk[8 * h + i + 1], w2, bmul2(kk[8 * h + i], w3)))), o[i]);
            if (h == 0) {
#pragma unroll
              for (int i = 11; i < 19; i++) kk[i] = lds32(ka + i * 64);
            }
            __syncwarp();
            sts128(ka + so + h * 512, __byte_perm(o[1], o[0], 0x5410), __byte_perm(o[3], o[2], 0x5410), __byte_perm(o[5], o[4], 0x5410), __byte_perm(o[7], o[6], 0x5410));
            sts128(ka + so + h * 512 + 1024, __byte_perm(o[1], o[0], 0x7632), __byte_perm(o[3], o[2], 0x7632), __byte_perm(o[5], o[4], 0x7632), __byte_perm(o[7], o[6], 0x7632));
          }
          asm volatile("fence.proxy.async.shared::cta;" ::: "memory");
          __syncwarp();
          if (lane == 0) {
            const int blk = (b & 1) * 10 + 2 * pg + hw;
            asm volatile("cp.async.bulk.tensor.5d.global.shared::cta.bulk_group [%0, {%2,%3,%3,%3,%4}], [%1];" ::"l"(&maps.xs), "r"(ka + vo), "r"(rc * 16), "r"(0), "r"((blk / 5) * 160 + blk % 5) : "memory");
          }
          ka += 8576;
        }
        if (lane == 0) {
          asm volatile("cp.async.bulk.commit_group;" ::: "memory");
          asm volatile("cp.async.bulk.wait_group.read 0;" ::: "memory");
        }
        bar_sync(3, 64);
        if (ht == 0) {
          TS1(12);
          mbar_expect_tx(BAR(B_HR), 20480);
          for (int c = 0; c < 5; c++) bulk_g2s(sb + SM_D + 128 + c * TP + 4128, P.ssm_k + (size_t)(ch0 + 32 * c) * 2048, 4096, BAR(B_HR));
        }
        uint32_t old = 0;
        if (lane == 0) {
          asm volatile("cp.async.bulk.wait_group 0;" ::: "memory");
          mbar_arrive(BAR(B_KD));
          if (hw) {
            TS1(6);
            mbar_wait(BAR(B_KD), 0);
            TS1(20);
            asm volatile("atom.relaxed.gpu.global.add.u32 %0, [%1], 1;" : "=r"(old) : "l"(&g_cnt[0]) : "memory");
          }
        }
        __syncwarp();
        if (lane < 20) sts128(sb + SM_D + 96 + (lane >> 2) * TP + ((lane >> 1) & 1) * 4128 + (lane & 1) * 16, 0, 0, 0, 0);
        uint32_t dv = 0;
        if (ht < 5) dv = __ldg((const unsigned short*)(P.ssm_D + ch0 + 32 * ht));
        if (lane == 0) TS1(hw ? 9 : 10);
        mbar_wait(BAR(B_HR), 0);
        if (ht == 0) TS1(11);
        if (ht < 5) {
          const uint32_t a0 = sb + SM_D + 128 + 4128 + ht * TP;
          asm volatile("st.shared.u32 [%0], %1;" ::"r"(a0), "r"(badd2(lds32(a0), dv)) : "memory");
        }
        __syncwarp();
        if (ht == 32) TS1(13);
#pragma unroll 1
        for (int c = 0; c < 5; c++) {
          const uint32_t d = sb + SM_D + 128 + c * TP + hw * 2048 + lane * 16;
          uint4 v[4]; uint32_t pv[4];
#pragma unroll
          for (int i = 0; i < 4; i++) { v[i] = lds128(d + 4128 + i * 512); pv[i] = lds32(d + 4124 + i * 512); }
#pragma unroll
          for (int i = 0; i < 4; i++)
            sts128(d + i * 512, __byte_perm(pv[i], v[i].x, 0x5432), __byte_perm(v[i].x, v[i].y, 0x5432), __byte_perm(v[i].y, v[i].z, 0x5432), __byte_perm(v[i].z, v[i].w, 0x5432));
          if (c == 1 && ht == 32) { asm volatile("st.shared.u32 [%0], %1;" ::"r"(sb + SM_BAR + 576), "r"((old & ~127u) + 128u) : "memory"); mbar_arrive(BAR(B_PRE)); TS1(8); }
        }
        __syncwarp();
        if (lane == 0) { mbar_arrive(BAR(B_HC)); if (hw) TS1(14); }
        __syncwarp();
        mbar_wait(BAR(B_WD), 0);
        if (ht == 32) TS1(34);
        {
          const uint32_t wl = (lane & 7) * 64 + (((lane >> 3) ^ ((lane & 7) >> 1)) << 4);
          const uint32_t wd = (lane >> 2) * 64 + (((lane ^ (lane >> 3)) & 3) << 4) - wl;
          uint32_t wa = sb + SM_X + hw * 8192 + wl;
#pragma unroll 1
          for (int i = 0; i < 16 / WU; i++, wa += WU * 512) {
            uint4 v[WU];
#pragma unroll
            for (int e = 0; e < WU; e++) v[e] = ldsm4(wa + e * 512);
#pragma unroll
            for (int e = 0; e < WU; e++) sts128(wa + wd + e * 512, v[e].x, v[e].y, v[e].z, v[e].w);
          }
        }
        asm volatile("fence.proxy.async.shared::cta;" ::: "memory");
        bar_sync(3, 64);
        if (ht == 32) {
          TS1(35);
          if (b < 120) bulk_s2g(g_wd + (size_t)b * 16384, sb + SM_X, 16384);
          asm volatile("cp.async.bulk.commit_group;" ::: "memory");
          asm volatile("cp.async.bulk.wait_group 0;" ::: "memory");
          mbar_arrive(BAR(B_WP));
          flag_add_relaxed(&g_cnt[45 * 32], 1);
          TS1(29);
        }
        if (lane == 0) {
          mbar_wait(BAR(B_HS + hw), 0);
          TS1(5 + hw * 10);
          bulk_s2g(g_h + ((size_t)(rt * 2 + hw) * 24 + ct * 3) * 8192, sb + SM_W + (1 + hw) * 24576, 24576);
          bulk_s2g(g_gate + rt * 128 + hw * 64 + ct * 8, sb + SM_GO + hw * 32, 32);
          asm volatile("cp.async.bulk.commit_group;" ::: "memory");
          asm volatile("cp.async.bulk.wait_group.read 0;" ::: "memory");
          mbar_arrive(BAR(B_HF + hw));
          asm volatile("cp.async.bulk.wait_group 0;" ::: "memory");
          flag_add_relaxed(&g_cnt[(1 + rt * 2 + hw) * 32], 16);
          TS1(26 + hw);
        }
        __syncwarp();
      }
      if (tid == 320) {
#pragma unroll 1
        for (int c = 0; c < 5; c++) {
          mbar_wait(BAR(B_ZR + c), 0);
          TS1(c < 4 ? 16 + c : 28);
          const uint32_t ps = sb + (c >= RM ? SM_D + 128 + c * TP : c < 2 ? SM_R2 + c * 57344 : SM_W + 24576), pp = c < 2 ? 28672 : 8192;
          uint8_t* zd = g_z + (size_t)(ch0 + 32 * c) * 4096;
          bulk_s2g(zd, ps, 4096);
          asm volatile("cp.async.bulk.commit_group;" ::: "memory");
          if (c == 1) {
            mbar_expect_tx(BAR(B_Q), 16384);
            for (int i = 0; i < 4; i++) tma3d(sb + SM_D + i * 4096, &maps.q, BAR(B_Q), 0, rb * 64, cb * 5 + i);
          }
          if (c < RM) {
            asm volatile("cp.async.bulk.wait_group 0;" ::: "memory");
#pragma unroll
            for (int i = 1; i < 4; i++)
              asm volatile("cp.reduce.async.bulk.global.shared::cta.bulk_group.add.noftz.bf16 [%0], [%1], %2;" ::"l"(zd + i * 256), "r"(ps + (i >> 1) * pp + (i & 1) * 4096), "r"(4096 - i * 256) : "memory");
            asm volatile("cp.async.bulk.commit_group;" ::: "memory");
          }
          asm volatile("cp.async.bulk.wait_group.read 0;" ::: "memory");
          mbar_arrive(BAR(B_KV + c));
          if (c == 1) TS1(23);
          asm volatile("cp.async.bulk.wait_group 0;" ::: "memory");
          if (c == 0 || c >= 3) flag_add_relaxed(&g_cnt[(c ? 25 + c * 4 + cb : 33 + cb) * 32], 4);
        }
        TS1(30);
      }
      if (tid == 288) {
        mbar_wait(BAR(B_PRE), 0);
        const uint32_t target = lds32v(sb + SM_BAR + 576);
        mbar_wait(BAR(B_KV + 2), 1);
        mbar_expect_tx(BAR(B_Z), 20480);
        mbar_expect_tx(BAR(B_Z + 1), 4096);
        tma3d(sb + SM_D + 16384, &maps.q, BAR(B_Z), 0, rb * 64, cb * 5 + 4);
        flag_wait(&g_cnt[(33 + cb) * 32], target);
        TS1(21);
        tma2d(sb + SM_D + 20480, &maps.z, BAR(B_Z), rb * 64, cb * 160);
        flag_wait(&g_cnt[(37 + cb) * 32], target);
        TS1(22);
        {
          mbar_wait(BAR(B_ZR + 4), 0);
#pragma unroll 1
          for (int c = 1; c < 4; c++) tma2d(sb + SM_W + (c - 1) * 4096, &maps.z, BAR(B_Z), rb * 64, cb * 160 + 32 * c);
        }
        TS1(24);
        flag_wait(&g_cnt[(41 + cb) * 32], target);
        TS1(31);
        {
          tma2d(sb + SM_W + 12288, &maps.z, BAR(B_Z + 1), rb * 64, cb * 160 + 128);
        }
      }
    }
  } else {
    {
      uint32_t tq;
      asm volatile("mov.u32 %0, %%tid.x;" : "=r"(tq));
      const int wi = __shfl_sync(0xffffffffu, tq >> 5, 0);
      if (elect_one()) {
#pragma unroll 1
        for (int gi = wi + 1; gi < 12; gi += 8) {
          const uint32_t cnt = gi < 5 ? 1 : (uint32_t)(0x80808102040908ull >> (8 * (gi - 5))) & 0xff;
#pragma unroll
          for (int j = 0; j < 6; j++) mbar_init(BAR(gi * 6 + j), cnt);
        }
        asm volatile("fence.proxy.async.shared::cta;" ::: "memory");
      }
      __syncwarp();
    }
    bar_sync(0, 384);
    asm volatile("setmaxnreg.inc.sync.aligned.u32 232;");
    const int t128 = tid & 127, w = __shfl_sync(0xffffffffu, t128 >> 5, 0), lane = tid & 31;
    const uint32_t ra0 = sb + SM_D + 128 + (((lane >> 2) & 1) ? 4128 + 2 * (128 * w + (lane >> 2) - 2 * (lane & 3) - 9) : 2 * (128 * w + (lane >> 2) - 2 * (lane & 3) - 8));
    uint32_t A0[16], A1[16], A2[16];
    {
      float ag[96], au[96];
      const uint64_t dA0 = mkdesc(sb + SM_X + wg * 8192, 16, 1024, 1);
      const uint64_t dB0 = mkdesc(sb + SM_W, 4096, 1024, 1);
      const uint32_t xa = sb + SM_X + wg * 8192 + (16 * w + (lane & 15)) * 128 + (((lane >> 4) ^ (lane & 7)) << 4);
      uint4 A[2];
      TS(18);
      mbar_wait(BAR(B_FX + 0), 0);
      TS(19);
      A[0] = ldsm4(xa);
#pragma unroll
      for (int st = 0; st < 28; st++) {
        const int k = st >> 2, kk = st & 3, n = st >> 1, xs = k % 3;
        if (!(st & 1)) mbar_w<1>(BAR(B_FW + n % 5), (n / 5) & 1);
        if (LSTEP && st > 0 && st % (LSTEP + !LSTEP) == 0) bar_sync(7, 256);
        if (kk == 0) TS(20 + k);
        if (st == SW && wg) {
          if (st == 26) {
            WG_WAIT(0);
            A[1] = ldsm4((xa ^ (3 << 5)) + xs * 16384);
            if (lane == 0) mbar_arrive(BAR(B_EW + (n - 1) % 5));
          }
          if (lane == 0) mbar_arrive(BAR(B_EX + xs) + ((A[0].x | A[1].x) & zz));
          bar_sync(4, 256);
        }
        WG_FENCE();
        wgmma_rs_tb_n192(ag, A[st & 1], dB0 + (n % 5) * 1536 + (st & 1) * 128, st > 0);
        wgmma_rs_tb_n192(au, A[st & 1], dB0 + (n % 5) * 1536 + 768 + (st & 1) * 128, st > 0);
        WG_COMMIT();
        if (kk == 3 && lane == 0 && !(k == 6 && SW < 28 && wg)) mbar_arrive(BAR(B_EX + xs));
        WG_WAIT(1);
        if (!(st & 1) && st > 0 && lane == 0 && !(st == SW && wg)) mbar_arrive(BAR(B_EW + (n - 1) % 5));
        if (kk < 3) { if (!(st == 26 && SW == 26 && wg)) A[(kk + 1) & 1] = ldsm4((xa ^ ((kk + 1) << 5)) + xs * 16384); }
        else if (k < 6) { mbar_w<1>(BAR(B_FX + (k + 1) % 3), ((k + 1) / 3) & 1); A[0] = ldsm4(xa + ((k + 1) % 3) * 16384); }
      }
      TS(1);
#define G1_UNITS(acc, xsl, wsl) { WG_FENCE(); _Pragma("unroll") for (int kk = 0; kk < 4; kk++) { wgmma_ss_tb_n192(acc, dA0 + (xsl) * 1024 + kk * 2, dB0 + (wsl) * 1536 + (kk >> 1) * 768 + (kk & 1) * 128, 1); if (kk == 3 - HOFF) WG_COMMIT(); } WG_COMMIT(); }
#define G1_UNIT(acc, xsl, wsl) { WG_FENCE(); _Pragma("unroll") for (int kk = 0; kk < 4; kk++) wgmma_ss_tb_n192(acc, dA0 + (xsl) * 1024 + kk * 2, dB0 + (wsl) * 1536 + (kk >> 1) * 768 + (kk & 1) * 128, 1); WG_COMMIT(); }
      mbar_w<2>(BAR(B_FX + 1), 0);
      mbar_w<2>(BAR(B_FW + 4), 0);
      if (SW == 28 && wg) {
        WG_WAIT(0);
        if (lane == 0) mbar_arrive(BAR(B_EW + 3));
        bar_sync(4, 256);
      }
      TS(8);
      G1_UNIT(ag, 1, 4);
      WG_WAIT(1);
      if (lane == 0 && (SW < 28 || !wg)) mbar_arrive(BAR(B_EW + 3));
      mbar_w<2>(BAR(B_FX + 2), 0);
      mbar_w<2>(BAR(B_FW + 0), 1);
      TS(6);
      G1_UNIT(ag, 2, 0);
      WG_WAIT(1);
      if (lane == 0) mbar_arrive(BAR(B_EW + 4));
      TS(9);
      mbar_w<2>(BAR(B_F9), 0);
      mbar_w<2>(BAR(B_FW + 1), 1);
      TS(16);
      G1_UNITS(ag, 3, 1);
      WG_WAIT(1);
      bar_arrive(4 + wg, 256);
      TS(14);
      if (lane == 0) mbar_arrive(BAR(B_EW + 0));
      WG_WAIT(0);
      if (lane == 0) mbar_arrive(BAR(B_EW + 1));
      TS(2);
      uint32_t sg[48], dep;
#define SIG(lo, hi) dep = sig_range<lo, hi>(ag, sg, zz);
#define U1(xsl, wsl, kk) wgmma_ss_tb_n192(au, dA0 + (xsl) * 1024 + kk * 2, dB0 + ((wsl) * 1536 + (kk >> 1) * 768 + (kk & 1) * 128 + dep), 1);
#define SGC(S0, S1, n) (((S0) + (n) * (S1)) < 48 ? ((S0) + (n) * (S1)) : 48)
#define UPHASE(S0, S1, WGI) { \
      SIG(0, S0) \
      TS(15); \
      mbar_w<4>(BAR(B_FW + 2) + dep, 1); \
      mbar_w<4>(BAR(B_FW + 3), 1); \
      bar_sync(5 + (WGI), 256); \
      TS(17); \
      WG_FENCE(); \
      U1(1, 2, 0) U1(1, 2, 1) U1(1, 2, 2) SIG(SGC(S0, S1, 0), SGC(S0, S1, 1)) \
      U1(1, 2, 3) WG_COMMIT(); SIG(SGC(S0, S1, 1), SGC(S0, S1, 2)) \
      U1(2, 3, 0) SIG(SGC(S0, S1, 2), SGC(S0, S1, 3)) \
      U1(2, 3, 1) SIG(SGC(S0, S1, 3), SGC(S0, S1, 4)) \
      U1(2, 3, 2) SIG(SGC(S0, S1, 4), SGC(S0, S1, 5)) \
      U1(2, 3, 3) WG_COMMIT(); SIG(SGC(S0, S1, 5), 48) \
      WG_WAIT(1); \
      if (lane == 0) mbar_arrive(BAR(B_EW + 2)); \
      TS(10); \
      mbar_w<4>(BAR(B_FW + 4) + dep, 1); \
      G1_UNITS(au, 3, 4); \
      if (LA) { WG_WAIT(1); if (!(WGI)) bar_arrive(6, 256); } \
      mbar_w<4>(BAR(B_HC), 0); \
      conv_ldA<0, 0>(A0, ra0 + (WGI) * TP, zz); conv_ldA<128, 0>(A1, ra0 + (WGI) * TP, zz); \
      if (!LA) { WG_WAIT(1); if (!(WGI)) bar_arrive(6, 256); } \
      TS(3); \
      mbar_w<4>(BAR(B_EW + 1 + (WGI)), 1);     \
      WG_WAIT(0); }
      UPHASE(SG0, SG1, wg)
      if (lane == 0) mbar_arrive(BAR(B_G1));
      TS(4);
      const uint32_t hb = sb + SM_W + (1 + wg) * 24576 + (16 * w + (lane & 15)) * 128;
#pragma unroll
      for (int j = 0; j < 24; j += 2) {
        uint32_t p[4];
#pragma unroll
        for (int e = 0; e < 4; e++) p[e] = bmul2(sg[2 * j + e], pack_bf16(au[4 * j + 2 * e], au[4 * j + 2 * e + 1]));
        const int cc = (j & 7) + (lane >> 4);
        stsm4(hb + (j >> 3) * 8192 + ((cc ^ (lane & 7)) << 4), p[0], p[1], p[2], p[3]);
      }
      asm volatile("fence.proxy.async.shared::cta;" ::: "memory");
      mbar_arrive(BAR(B_HS + wg));
      TS(5);
    }
      uint32_t pb = sb + SM_R2 + wg * 57344, pitch = 28672;
      const uint32_t po = (w & 1) * 4096 + (lane >> 4) * 256 + (lane & 4) * 32 + (((lane >> 1) ^ lane) & 4) * 16 + (lane & 3) * 16;
      mbar_w<16>(BAR(B_XI), 0);
      conv_dupA(A0, zz); conv_dupA(A1, zz);
      if (SHB) asm volatile("xor.b32 %0, %1, %2;" : "=r"(A1[2]) : "r"(A0[13]), "r"(zz));
#pragma unroll 1
      for (int c = wg; c < 4; c += 2) {
        const uint32_t ra = ra0 + c * TP;
        const uint64_t dX = mkdesc(sb + SM_W + c * XCH + 256, XP, 128, 0);
        float T0[64], T1[16], T2[32], T3[16];
        TS(27 + (c >> 1));
        WG_FENCE();
#pragma unroll
        for (int s = 0; s < 8; s++) {
          wgmma_rs<128>(T0, (s < 4 ? A0 : A1 - 16) + 4 * s, dX - s, s > 0);
          if (s == 3 || s == 7) WG_COMMIT();
        }
        if (c >= 2) { pb = sb + SM_W + (1 + wg) * 24576; pitch = 8192; }
        conv_ldA<3072>(A2, ra, zz);
        conv_grp<32, 0>(T3, A2, dX);
        WG_WAIT(2); conv_ldA<3072 + 128>(A0, ra, zz, A2);
        conv_grp<32, 1>(T3, A0, dX);
        WG_WAIT(2); conv_ldA<1024>(A1, ra, zz);
        conv_grp2<0>(T2, T1, A1, dX);
        WG_WAIT(2); conv_ldA<1024 + 128>(A2, ra, zz, A1);
        conv_grp2<1>(T2, T1, A2, dX);
        WG_WAIT(2); conv_ldA<2048>(A0, ra, zz);
        conv_grp<64, 0, 1>(T2, A0, dX);
#pragma unroll
        for (int i = 0; i < 16; i++) fadd_v(T0[48 + i], T3[i]);
        WG_WAIT(2); conv_ldA<2048 + 128>(A1, ra, zz, A0);
        conv_grp<64, 1>(T2, A1, dX);
        WG_WAIT(2);
#pragma unroll
        for (int i = 0; i < 16; i++) fadd_v(T0[16 + i], T1[i]);
        const uint32_t rn = c < 2 ? ra + 2 * TP : ra0 + 4 * TP + (wg ? 0 : 1024);
        WG_WAIT(1); conv_ldA<0>(A0, rn, zz);
        mbar_w<16>(BAR(c < 2 ? B_G1 : B_HF + wg), 0);
        if (c == 1) mbar_w<16>(BAR(B_WP), 0);
        const uint32_t pa = pb + po + (w >> 1) * pitch;
#pragma unroll
        for (int j = 0; j < 8; j += 2)
          stsm4t(pa + j * 256, pack_bf16(T0[4 * j], T0[4 * j + 1]), pack_bf16(T0[4 * j + 2], T0[4 * j + 3]), pack_bf16(T0[4 * j + 4], T0[4 * j + 5]), pack_bf16(T0[4 * j + 6], T0[4 * j + 7]));
        WG_WAIT(0); conv_ldA<128>(A1, rn, zz, A0);
        TS(30 + (c >> 1));
#pragma unroll
        for (int i = 0; i < 32; i++) T0[32 + i] += T2[i];
#pragma unroll
        for (int j = 8; j < 16; j += 2)
          stsm4t(pa + j * 256, pack_bf16(T0[4 * j], T0[4 * j + 1]), pack_bf16(T0[4 * j + 2], T0[4 * j + 3]), pack_bf16(T0[4 * j + 4], T0[4 * j + 5]), pack_bf16(T0[4 * j + 6], T0[4 * j + 7]));
        if (c < RM) red_fin(BAR(B_ZR + c));
      }
      const uint32_t ra = ra0 + 4 * TP;
      const uint64_t dX = mkdesc(sb + SM_W + 4 * XCH + 256, XP, 128, 0);
      uint4 v[2][4];
      TS(29);
#define PST(pa, T, j) stsm4t(pa, pack_bf16(T[4 * (j)], T[4 * (j) + 1]), pack_bf16(T[4 * (j) + 2], T[4 * (j) + 3]), pack_bf16(T[4 * (j) + 4], T[4 * (j) + 5]), pack_bf16(T[4 * (j) + 6], T[4 * (j) + 7]))
    const int g = lane >> 2;
    const int frow = 16 * w + (lane & 7) + 8 * ((lane >> 3) & 1);
    const uint32_t fo = frow * 64 + (((lane >> 4) ^ ((frow >> 1) & 3)) << 4);

    if (wg == 0) {
      float acc[80];
      const uint64_t dA0 = mkdesc(sb, 16, 1024, 1), dB0 = mkdesc(sb, 4096, 512, 2);
      {
        float T1[16], T2[32];
#pragma unroll
        for (int c = 0; c < EF; c++) {
          mbar_wait(BAR(B_F2 + g2s(c)), g2u(c) & 1);
          WG_FENCE();
#pragma unroll
          for (int kk = 0; kk < 4; kk++) {
            wgmma_ss_tb_n160(acc, dA0 + (g2A(c) / 16 + kk * 2), dB0 + (g2b(g2s(c)) / 16 + kk * 64), c > 0 || kk > 0);
            if (kk == 3) WG_COMMIT();
            if (4 * c + kk == RE0) { bar_sync(1, 128); red_ld(v, sb + SM_W + 24576, t128); }
            if (4 * c + kk == RE1) red_st(v, sb + SM_D + 128 + 2 * TP, t128);
            if (4 * c + kk == RE2) { red_fin(BAR(B_ZR + 2)); TS(34); }
          }
          if (c > 0) { WG_WAIT(1); if (lane == 0) mbar_arrive(BAR(B_E2 + g2s(c - 1))); }
        }
        TS(35);
        WG_FENCE();
#pragma unroll
        for (int s = 0; s < 8; s++) {
          wgmma_rs<64>(T2, (s < 4 ? A0 : A1 - 16) + 4 * s, dX + 32 - s, s > 0);
          wgmma_rs<32>(T1, (s < 4 ? A0 : A1 - 16) + 4 * s, dX - s, s > 0);
          if (s == 3 || s == 7) WG_COMMIT();
          if (EF && s == 3) { WG_WAIT(1); if (lane == 0) mbar_arrive(BAR(B_E2 + g2s(EF - 1))); WG_FENCE(); }
          if (RM <= 2 && !EF) {
            if (s == RQ0) { bar_sync(1, 128); red_ld(v, sb + SM_W + 24576, t128); }
            if (s == RQ1) red_st(v, sb + SM_D + 128 + 2 * TP, t128);
            if (s == RQ2) { red_fin(BAR(B_ZR + 2)); TS(34); }
          }
        }
        conv_ldA<2048>(A2, ra, zz);
        conv_grp<64, 0, 1>(T2, A2, dX);
        WG_WAIT(2); conv_ldA<2048 + 128>(A0, ra, zz, A2);
        conv_grp<64, 1>(T2, A0, dX);
        bar_sync(8, 256);
        const uint32_t pa = sb + SM_W + po + (w >> 1) * 8192 + 1024;
        WG_WAIT(2);
        PST(pa, T1, 0); PST(pa + 512, T1, 2);
        mbar_wait(BAR(B_F2 + g2s(EF)), g2u(EF) & 1);
        WG_FENCE();
#pragma unroll
        for (int kk = 0; kk < 4; kk++) wgmma_ss_tb_n160(acc, dA0 + (g2a(g2s(EF)) / 16 + kk * 2), dB0 + (g2b(g2s(EF)) / 16 + kk * 64), EF || kk > 0);
        WG_COMMIT();
        WG_WAIT(1);
        TS(32);
#pragma unroll
        for (int j = 0; j < 8; j += 2) PST(pa + 1024 + j * 256, T2, j);
        bar_arrive(7, 256);
        TS(7);
      }
      uint4 ga[10];
      uint32_t om[2];
      const uint32_t gb = sb + SM_D + (16 * w + g) * 64 + (((lane ^ (g >> 1)) & 3) << 4);
      uint8_t* go = P.out + (size_t)(rb * 64 + w * 16 + g) * 1280 + cb * 320 + (lane & 3) * 16;
#define LDGA(j) ga[j] = lds128m(gb + ((j) >> 1) * 4096 + ((j) & 1) * 512)
#pragma unroll
      for (int c = EF + EG; c < 24 - LS; c++) {
        if (SPN & 2) mbar_spin(BAR(B_F2 + g2s(c)), g2u(c) & 1); else mbar_wait(BAR(B_F2 + g2s(c)), g2u(c) & 1);
        if (c & 1) TS(36 + (c >> 1));
        WG_FENCE();
#pragma unroll
        for (int kk = 0; kk < 4; kk++) {
          wgmma_ss_tb_n160(acc, dA0 + (g2A(c) / 16 + kk * 2), dB0 + (g2b(g2s(c)) / 16 + kk * 64), c > 0 || kk > 0);
          if (kk == PSP || kk == 3) WG_COMMIT();
          if (!GL && kk == PSP && c >= GC && c < GC + 8 / GN) {
            if (c == GC) {
              mbar_wait(BAR(B_PF), 0);
              const float gv0 = __uint_as_float(lds32(sb + SM_GT + (16 * w + g) * 4)), gv1 = __uint_as_float(lds32(sb + SM_GT + (16 * w + g + 8) * 4));
              om[0] = pack_bf16(1.0f - gv0, 1.0f - gv0); om[1] = pack_bf16(1.0f - gv1, 1.0f - gv1);
            }
#pragma unroll
            for (int j = 0; j < GN; j++) LDGA((c - GC) * GN + j);
          }
          if (kk == PSP && c > EF && c < 19) { WG_WAIT(1); if (lane == 0) mbar_arrive(BAR(B_E2 + g2s(c - 1))); }
        }
      }
#define OUT(j, acc) { const float* a = (acc) + 16 * ((j) >> 1) + 2 * ((j) & 1); \
        stg128(go + ((j) & 1) * 10240 + ((j) >> 1) * 64, badd2(ga[j].x, bmul2(om[(j) & 1], pack_bf16(a[0], a[1]))), badd2(ga[j].y, bmul2(om[(j) & 1], pack_bf16(a[4], a[5]))), \
               badd2(ga[j].z, bmul2(om[(j) & 1], pack_bf16(a[8], a[9]))), badd2(ga[j].w, bmul2(om[(j) & 1], pack_bf16(a[12], a[13])))); }
      constexpr int C0 = 24 - LS;
      static_assert(SW >= 26 && LS <= 5 && GC + 8 / GN <= C0, "");
      float ab[80 - NA / 2];
#define GB(c) { _Pragma("unroll") for (int kk = 0; kk < 4; kk++) MMA_B(ab, dA0 + (g2A(c) / 16 + kk * 2), dB0 + (g2b(g2s(c)) / 16 + NA * 8 + kk * 64), c > C0 || kk > 0); }
      mbar_wait(BAR(B_F2 + g2s(C0)), g2u(C0) & 1);
      WG_FENCE();
      GB(C0)
      WG_COMMIT();
      WG_WAIT(1);
#pragma unroll
      for (int c = C0; c < 24; c++) {
        if (c == 23 && NB0) {
          WG_FENCE();
#pragma unroll
          for (int e = C0 + 1; e < C0 + 1 + NB0; e++) GB(e)
        }
        if (c == 23) { TS(11); mbar_wait(BAR(GL == 2 ? B_PF : B_GA), 0); }
        if (c > C0) { if (SPN & 2) mbar_spin(BAR(B_F2 + g2s(c)), g2u(c) & 1); else mbar_wait(BAR(B_F2 + g2s(c)), g2u(c) & 1); }
        if (c == 23) {
          if (GL) {
            const float gv0 = __uint_as_float(lds32(sb + SM_GT + (16 * w + g) * 4)), gv1 = __uint_as_float(lds32(sb + SM_GT + (16 * w + g + 8) * 4));
            om[0] = pack_bf16(1.0f - gv0, 1.0f - gv0); om[1] = pack_bf16(1.0f - gv1, 1.0f - gv1);
          }
#pragma unroll
          for (int j = GL ? 0 : 8; j < (GL == 2 ? 8 : 10); j++) LDGA(j);
        }
        if (c & 1) TS(36 + (c >> 1));
        WG_FENCE();
#pragma unroll
        for (int kk = 0; kk < 4; kk++) MMA_A(acc, dA0 + (g2A(c) / 16 + kk * 2), dB0 + (g2b(g2s(c)) / 16 + kk * 64), 1);
        if (c == C0 + BD) {
          WG_COMMIT();
          WG_WAIT(1);
#pragma unroll
          for (int i = 0; i < 80 - NA / 2; i++) fadd_v(ab[i], acc[NA / 2 + i]);
        }
      }
      WG_COMMIT();
      WG_FENCE();
#pragma unroll
      for (int c = C0 + 1 + NB0; c < C0 + 1 + NB0 + NB1; c++) GB(c)
      WG_COMMIT();
      TS(21);
      WG_WAIT(1);
      TS(33);
#pragma unroll
      for (int j = 0; j < NA / 16; j++) {
        if (j == E1 && C0 + 1 + NB0 + NB1 < 24) {
          TS(22);
          WG_FENCE();
#pragma unroll
          for (int c = C0 + 1 + NB0 + NB1; c < 24; c++) GB(c)
          WG_COMMIT();
          TS(23);
        }
        OUT(j, acc)
      }
      TS(26);
      if (GL == 2) { mbar_wait(BAR(B_GA), 0); LDGA(8); LDGA(9); }
      TS(25);
      WG_WAIT(0);
      TS(12);
#pragma unroll
      for (int j = NA / 16; j < 10; j++) OUT(j, ab - NA / 2)
      TS(13);
    } else {
      {
        float T0[64], T3[16];
        bar_arrive(8, 256);
        WG_FENCE();
#pragma unroll
        for (int s = 0; s < 8; s++) {
          wgmma_rs<128>(T0, (s < 4 ? A0 : A1 - 16) + 4 * s, dX - s, s > 0);
          if (s == 3 || s == 7) WG_COMMIT();
          if (s == RP0) { bar_sync(2, 128); red_ld(v, sb + SM_W + 49152, t128); }
          if (s == RP1) red_st(v, sb + SM_D + 128 + 3 * TP, t128);
          if (s == RP2) { red_fin(BAR(B_ZR + 3)); TS(34); }
        }
        conv_ldA<3072>(A2, ra, zz);
        conv_grp<32, 0>(T3, A2, dX);
        WG_WAIT(2); conv_ldA<3072 + 128>(A0, ra, zz, A2);
        conv_grp<32, 1>(T3, A0, dX);
        const uint32_t pa = sb + SM_W + po + (w >> 1) * 8192;
        bar_sync(7, 256);
        uint4 u[6];
#pragma unroll
        for (int j = 0; j < 6; j++) u[j] = ldsm4t(pa + 1024 + j * 512);
        WG_WAIT(2);
        PST(pa, T0, 0); PST(pa + 512, T0, 2);
#define PSTA(j) stsm4t(pa + (j) * 256, badd2(u[(j) / 2 - 2].x, pack_bf16(T0[4 * (j)], T0[4 * (j) + 1])), badd2(u[(j) / 2 - 2].y, pack_bf16(T0[4 * (j) + 2], T0[4 * (j) + 3])), \
                       badd2(u[(j) / 2 - 2].z, pack_bf16(T0[4 * (j) + 4], T0[4 * (j) + 5])), badd2(u[(j) / 2 - 2].w, pack_bf16(T0[4 * (j) + 6], T0[4 * (j) + 7])))
#pragma unroll
        for (int j = 4; j < 12; j += 2) PSTA(j);
        WG_WAIT(0);
        TS(32);
#pragma unroll
        for (int i = 0; i < 16; i++) T0[48 + i] += T3[i];
        PSTA(12); PSTA(14);
        TS(7);
        bar_sync(2, 128);
        if (XA < 23 && t128 == 0) mbar_arrive(BAR(B_GF));
        TS(1);
        red_ld(v, sb + SM_W, t128);
        red_st(v, sb + SM_D + 128 + 4 * TP, t128);
        TS(2);
        red_fin(BAR(B_ZR + 4));
      }
      TS(35);
      const uint32_t zo = sb + ((lane & 7) + 8 * (lane >> 4)) * 128 + (((w + ((((lane >> 3) ^ rb) & 1) << 2)) ^ (lane & 7)) << 4);
      mbar_wait(BAR(B_Q), 0);
      mbar_wait(BAR(B_Z), 0);
      TS(10);
      uint4 zr[10], qr[10];
#pragma unroll
      for (int j = 0; j < 10; j++) { if (j < 8) zr[j] = ldsm4t(zo + (j < 2 ? SM_D + 20480 : SM_W - 4096) + j * 2048); qr[j] = ldsm4(sb + SM_D + (j >> 1) * 4096 + (fo ^ ((j & 1) << 5))); }
      const float gv0 = __uint_as_float(lds32(sb + SM_GT + (16 * w + g) * 4)), gv1 = __uint_as_float(lds32(sb + SM_GT + (16 * w + g + 8) * 4));
      const uint32_t g0 = pack_bf16(gv0, gv0), g1 = pack_bf16(gv1, gv1);
#pragma unroll
      for (int j = 0; j < 10; j++) {
        if (j == 8) { if (GL != 1) mbar_arrive(BAR(B_PF)); TS(12); mbar_wait(BAR(B_Z + 1), 0);
          TS(11); zr[8] = ldsm4t(zo + SM_W + 6 * 2048); zr[9] = ldsm4t(zo + SM_W + 7 * 2048); }
        stsm4(sb + SM_D + (j >> 1) * 4096 + (fo ^ ((j & 1) << 5)), bmul2(g0, bmul2(qr[j].x, zr[j].x)), bmul2(g1, bmul2(qr[j].y, zr[j].y)), bmul2(g0, bmul2(qr[j].z, zr[j].z)), bmul2(g1, bmul2(qr[j].w, zr[j].w)));
      }
      mbar_arrive(BAR(B_GA));
      TS(13);
    }
  }
}

typedef CUresult (*EncFn)(CUtensorMap*, CUtensorMapDataType, cuuint32_t, void*, const cuuint64_t*, const cuuint64_t*, const cuuint32_t*, const cuuint32_t*,
                          CUtensorMapInterleave, CUtensorMapSwizzle, CUtensorMapL2promotion, CUtensorMapFloatOOBfill);

void enc(EncFn fn, CUtensorMap* m, CUtensorMapDataType dt, int rank, const void* p, const cuuint64_t* gd, const cuuint64_t* gs, const cuuint32_t* bd, CUtensorMapSwizzle sw) {
  cuuint32_t es[5] = {1, 1, 1, 1, 1};
  fn(m, dt, rank, (void*)p, gd, gs, bd, es, CU_TENSOR_MAP_INTERLEAVE_NONE, sw, CU_TENSOR_MAP_L2_PROMOTION_L2_128B, CU_TENSOR_MAP_FLOAT_OOB_FILL_NONE);
}

}

extern "C" void kernel_launch(void* const* d_in, const int* in_sizes, int n_in, void* d_out, int out_size) {
  static EncFn fn = nullptr;
  static void *zp = nullptr, *xp = nullptr;
  if (!fn) {
    cudaGetSymbolAddress(&zp, g_z);
    cudaGetSymbolAddress(&xp, g_X);
    void* f = nullptr; cudaDriverEntryPointQueryResult qr;
    cudaGetDriverEntryPoint("cuTensorMapEncodeTiled", &f, cudaEnableDefault, &qr);
    fn = (EncFn)f;
    cudaFuncSetAttribute(fused_kernel, cudaFuncAttributeMaxDynamicSharedMemorySize, SM_TOTAL);
  }
  Maps m;
  const CUtensorMapDataType BF = CU_TENSOR_MAP_DATA_TYPE_BFLOAT16;
  { cuuint64_t gd[2] = {640, 2048}, gs[1] = {1280}; cuuint32_t bd[2] = {64, 128}; enc(fn, &m.x, BF, 2, d_in[0], gd, gs, bd, CU_TENSOR_MAP_SWIZZLE_128B); }
  { cuuint64_t gd[3] = {64, 640, 24}, gs[2] = {3072, 128}; cuuint32_t bd[3] = {64, 32, 3};
    enc(fn, &m.wg, BF, 3, d_in[7], gd, gs, bd, CU_TENSOR_MAP_SWIZZLE_128B); enc(fn, &m.wu, BF, 3, d_in[8], gd, gs, bd, CU_TENSOR_MAP_SWIZZLE_128B); }
  { cuuint64_t gd[3] = {32, 1536, 20}, gs[2] = {1280, 64}; cuuint32_t bd[3] = {32, 64, 4}; enc(fn, &m.wd, BF, 3, d_in[9], gd, gs, bd, CU_TENSOR_MAP_SWIZZLE_64B); }
  { cuuint64_t gd[3] = {32, 2048, 20}, gs[2] = {1280, 64}; cuuint32_t bk[3] = {32, 35, 2}, bv[3] = {32, 32, 2};
    enc(fn, &m.k, BF, 3, d_in[1], gd, gs, bk, CU_TENSOR_MAP_SWIZZLE_NONE); enc(fn, &m.v, BF, 3, d_in[2], gd, gs, bv, CU_TENSOR_MAP_SWIZZLE_NONE); }
  { cuuint64_t gd[5] = {1024, 16, 2, 2, 485}, gs[4] = {40960, 2048, 20480, 4096}; cuuint32_t bd[5] = {16, 16, 2, 2, 1}; enc(fn, &m.xs, BF, 5, xp, gd, gs, bd, CU_TENSOR_MAP_SWIZZLE_NONE); }
  { cuuint64_t gd[3] = {64, 16, 1280}, gs[2] = {128, 2048}; cuuint32_t bd[3] = {64, 18, 10}; enc(fn, &m.xl, BF, 3, xp, gd, gs, bd, CU_TENSOR_MAP_SWIZZLE_NONE); }
  { cuuint64_t gd[3] = {32, 2048, 20}, gs[2] = {1280, 64}; cuuint32_t bd[3] = {32, 64, 5}, bq[3] = {32, 64, 1};
    enc(fn, &m.q, BF, 3, d_in[0], gd, gs, bq, CU_TENSOR_MAP_SWIZZLE_64B); enc(fn, &m.o, BF, 3, d_out, gd, gs, bd, CU_TENSOR_MAP_SWIZZLE_64B); }
  { cuuint64_t gd[2] = {2048, 640}, gs[1] = {4096}; cuuint32_t bd[2] = {64, 32}; enc(fn, &m.z, BF, 2, zp, gd, gs, bd, CU_TENSOR_MAP_SWIZZLE_128B); }
  Ptrs p;
  p.out = (uint8_t*)d_out; p.x = (const __nv_bfloat16*)d_in[0]; p.shift_k = (const __nv_bfloat16*)d_in[3]; p.ssm_k = (const __nv_bfloat16*)d_in[4];
  p.ssm_D = (const __nv_bfloat16*)d_in[5]; p.gate_w = (const __nv_bfloat16*)d_in[10];
  p.wg = (const __nv_bfloat16*)d_in[7]; p.wu = (const __nv_bfloat16*)d_in[8];
  fused_kernel<<<128, 384, SM_TOTAL, cudaStreamPerThread>>>(m, p, 0u);
}
```
